```python
import torch

def _softmax(x, axis=-1):
    return torch.softmax(x, dim=axis)
def _gelu(x):
    return torch.nn.functional.gelu(x, approximate="tanh")
def _silu(x):
    return torch.nn.functional.silu(x)
def _sigmoid(x):
    return torch.sigmoid(x)
def _layernorm(x, axis=-1, eps=1e-5):
    m = x.mean(dim=axis, keepdim=True)
    v = x.var(dim=axis, keepdim=True, unbiased=False)
    return (x - m) / torch.sqrt(v + eps)
def _scatter_add(tgt, idx, src, axis=0):
    return tgt.clone().index_add_(axis, idx, src)
def _segment_sum(src, seg, n):
    out = torch.zeros((n,) + src.shape[1:], dtype=src.dtype)
    return out.index_add_(0, seg, src)
def _pad(x, pw):
    flat = tuple(v for pair in reversed(pw) for v in pair)
    return torch.nn.functional.pad(x, flat)

kernel_name = 'gated_mix__linear_kernel_hedgehog__mixer_token_mlp__prompt'

def setup_inputs():

    _w = (lambda a: (lambda t: t.to(torch.bfloat16) if t.is_floating_point() else t)(torch.as_tensor(a)))
    def _A_setup():
        B, S, D, H = 1, 2048, 1024, 32
        Dh = D // H
        return {
            "x": _w((lambda *s: torch.randn(*s, dtype=torch.bfloat16) * 0.05)(B, S, D)),
            "wqkv": _w((lambda *s: torch.randn(*s, dtype=torch.bfloat16) * 0.8)(D, 3 * D)),
            "w_phi": _w((lambda *s: torch.randn(*s, dtype=torch.bfloat16) * 0.8)(H, Dh, Dh) * (Dh ** -0.5)),
            "wo": _w((lambda *s: torch.randn(*s, dtype=torch.bfloat16) * 0.05)(D, D)),
        }
    _A_in = _A_setup()

    def _B_setup():
        B, S, D, F = 1, 2048, 1024, 3584
        return {
            "x": _w((lambda *s: torch.randn(*s, dtype=torch.bfloat16) * 0.05)(B, S, D)),
            "w1": _w((lambda *s: torch.randn(*s, dtype=torch.bfloat16) * 0.8)(S, F) * (S ** -0.5)),
            "b1": _w((lambda *s: torch.randn(*s, dtype=torch.bfloat16) * 12.8)(F) * 0.02),
            "w2": _w((lambda *s: torch.randn(*s, dtype=torch.bfloat16) * 0.05)(F, S) * (F ** -0.5)),
            "b2": _w((lambda *s: torch.randn(*s, dtype=torch.bfloat16) * 0.8)(S) * 0.02),
        }
    _B_in = _B_setup()

    return {
        "A_x": _A_in["x"],
        "A_wqkv": _A_in["wqkv"],
        "A_w_phi": _A_in["w_phi"],
        "A_wo": _A_in["wo"],
        "B_x": _B_in["x"],
        "B_w1": _B_in["w1"],
        "B_b1": _B_in["b1"],
        "B_w2": _B_in["w2"],
        "B_b2": _B_in["b2"],
        "gate_w": _w((lambda *s: torch.randn(*s, dtype=torch.bfloat16) * 0.05)(1024) * 16.0),
    }

def reference(A_x, A_wqkv, A_w_phi, A_wo, B_x, B_w1, B_b1, B_w2, B_b2, gate_w):
    def _A_ref(x, wqkv, w_phi, wo):
        B, S, D = x.shape
        H = 32; Dh = D // H
        qkv = (lambda x, *d: x.permute(*d))((x @ wqkv).reshape(B, S, 3, H, Dh), 2, 0, 3, 1, 4)
        q, k, v = qkv[0], qkv[1], qkv[2]
        pq = torch.einsum("bhsd,hdf->bhsf", q, w_phi)
        pk = torch.einsum("bhsd,hdf->bhsf", k, w_phi)
        phi_q = torch.concatenate([_softmax(pq, axis=-1), _softmax(-pq, axis=-1)], axis=-1)
        phi_k = torch.concatenate([_softmax(pk, axis=-1), _softmax(-pk, axis=-1)], axis=-1)
        kv = torch.einsum("bhsf,bhsd->bhfd", phi_k, v)
        z  = torch.einsum("bhsf->bhf", phi_k)
        num = torch.einsum("bhqf,bhfd->bhqd", phi_q, kv)
        den = torch.einsum("bhqf,bhf->bhq", phi_q, z)[..., None] + 1e-6
        o = num / den
        return (lambda x, *d: x.permute(*d))(o, 0, 2, 1, 3).reshape(B, S, D) @ wo

    def _B_ref(x, w1, b1, w2, b2):
        B, S, D = x.shape
        h = _layernorm(x, axis=-1)
        u = torch.einsum("bsd,sf->bdf", h, w1) + b1
        u = _gelu(u)
        y = torch.einsum("bdf,fs->bds", u, w2) + b2
        return (lambda x, *d: x.permute(*d))(y, 0, 2, 1)

    x = A_x
    g = _sigmoid((x * gate_w).sum(-1, keepdims=True))
    a = _A_ref(x, A_wqkv, A_w_phi, A_wo)
    b = _B_ref(x, B_w1, B_b1, B_w2, B_b2)
    return g * a + (1 - g) * b
```

```cpp
#include <cuda_runtime.h>
#include <cuda.h>
#include <cuda_bf16.h>
#include <stdint.h>

namespace {

constexpr int S_ = 2048, D_ = 1024, F_ = 3584;
constexpr int NCTA = 128;
constexpr int NSTAGE = 3;
constexpr int SLOT = 49152;
constexpr int OFF_STG = NSTAGE * SLOT;
constexpr int STG_PITCH = 464;
constexpr int OFF_WPHI = OFF_STG + 59392;
constexpr int OFF_ONES = OFF_WPHI + 8192;
constexpr int OFF_BIAS = OFF_ONES + 1024;
constexpr int OFF_BAR = OFF_BIAS + 1024;
constexpr int SMEM_BYTES = OFF_BAR + 256 + 1024;
constexpr int N0 = 34;
constexpr int FB = F_ / 64;
constexpr int NTHREADS = 384;

constexpr int FL_LN = 0, FL_U = 1, FL_KV = 5, FL_O = 21, FL_PART = 37, FL_EXIT = 101, FL_COUNT = 102;

__device__ __align__(1024) __nv_bfloat16 g_h[S_ * D_];
__device__ __align__(1024) __nv_bfloat16 g_u[D_ * F_];
__device__ __align__(1024) __nv_bfloat16 g_o[S_ * D_];
__device__ __align__(1024) uint4 g_pq[NCTA * 2 * 2 * 4 * 128];
__device__ __align__(1024) float4 g_kvpart[NCTA * 2 * 5 * 128];
__device__ __align__(1024) uint4 g_part[64 * 16 * 256];
__device__ __align__(1024) float g_gate[S_];
__device__ __align__(1024) unsigned g_flags[FL_COUNT * 32];

__device__ __forceinline__ uint32_t smem_u32(const void* p) { return (uint32_t)__cvta_generic_to_shared(p); }
__device__ __forceinline__ void mbar_init(uint32_t bar, uint32_t cnt) {
    asm volatile("mbarrier.init.shared::cta.b64 [%0], %1;" ::"r"(bar), "r"(cnt));
}
__device__ __forceinline__ void mbar_expect_tx(uint32_t bar, uint32_t bytes) {
    asm volatile("mbarrier.arrive.expect_tx.shared::cta.b64 _, [%0], %1;" ::"r"(bar), "r"(bytes) : "memory");
}
__device__ __forceinline__ void mbar_arrive(uint32_t bar) {
    asm volatile("mbarrier.arrive.shared::cta.b64 _, [%0];" ::"r"(bar) : "memory");
}
__device__ __forceinline__ void mbar_arrive_cluster(uint32_t bar_cluster_addr) {
    asm volatile("mbarrier.arrive.shared::cluster.b64 _, [%0];" ::"r"(bar_cluster_addr) : "memory");
}
__device__ __forceinline__ uint32_t mapa(uint32_t addr, uint32_t cta) {
    uint32_t r;
    asm volatile("mapa.shared::cluster.u32 %0, %1, %2;" : "=r"(r) : "r"(addr), "r"(cta));
    return r;
}
template <int ROLE>
__device__ __forceinline__ void mbar_wait(uint32_t bar, uint32_t parity) {
    uint32_t done;
    int n = 0;
    do {
        asm volatile("{\n.reg .pred p;\nmbarrier.try_wait.parity.shared::cta.b64 p, [%1], %2;\nselp.u32 %0, 1, 0, p;\n}"
                     : "=r"(done) : "r"(bar), "r"(parity) : "memory");
    } while (!done && ++n < (1 << 16));
}
template <int ROLE>
__device__ __forceinline__ void wait_flag(const unsigned* p, unsigned target) {
    unsigned v;
    int n = 0;
    while (true) {
        asm volatile("ld.acquire.gpu.global.u32 %0, [%1];" : "=r"(v) : "l"(p) : "memory");
        if (v >= target) break;
        if (++n > (1 << 16)) {
            break;
        }
        __nanosleep(40);
    }
}
__device__ __forceinline__ void flag_add(unsigned* p) {
    asm volatile("fence.acq_rel.gpu;\nred.relaxed.gpu.global.add.u32 [%0], 1;" ::"l"(p) : "memory");
}
__device__ __forceinline__ void fence_async_smem() { asm volatile("fence.proxy.async.shared::cta;" ::: "memory"); }
__device__ __forceinline__ void fence_async_all() { asm volatile("fence.proxy.async;" ::: "memory"); }
__device__ __forceinline__ void bar_sync(int id, int n) { asm volatile("bar.sync %0, %1;" ::"r"(id), "r"(n) : "memory"); }

__device__ __forceinline__ void tma2d(uint32_t dst, const CUtensorMap* m, int c0, int c1, uint32_t bar) {
    asm volatile("cp.async.bulk.tensor.2d.shared::cluster.global.mbarrier::complete_tx::bytes [%0], [%1, {%3, %4}], [%2];"
                 ::"r"(dst), "l"((uint64_t)m), "r"(bar), "r"(c0), "r"(c1) : "memory");
}
__device__ __forceinline__ void tma2d_mc(uint32_t dst, const CUtensorMap* m, int c0, int c1, uint32_t bar) {
    asm volatile("cp.async.bulk.tensor.2d.shared::cluster.global.mbarrier::complete_tx::bytes.multicast::cluster [%0], [%1, {%3, %4}], [%2], %5;"
                 ::"r"(dst), "l"((uint64_t)m), "r"(bar), "r"(c0), "r"(c1), "h"((uint16_t)3) : "memory");
}
__device__ __forceinline__ void tma3d(uint32_t dst, const CUtensorMap* m, int c0, int c1, int c2, uint32_t bar) {
    asm volatile("cp.async.bulk.tensor.3d.shared::cluster.global.mbarrier::complete_tx::bytes [%0], [%1, {%3, %4, %5}], [%2];"
                 ::"r"(dst), "l"((uint64_t)m), "r"(bar), "r"(c0), "r"(c1), "r"(c2) : "memory");
}
__device__ __forceinline__ void tma3d_mc(uint32_t dst, const CUtensorMap* m, int c0, int c1, int c2, uint32_t bar) {
    asm volatile("cp.async.bulk.tensor.3d.shared::cluster.global.mbarrier::complete_tx::bytes.multicast::cluster [%0], [%1, {%3, %4, %5}], [%2], %6;"
                 ::"r"(dst), "l"((uint64_t)m), "r"(bar), "r"(c0), "r"(c1), "r"(c2), "h"((uint16_t)3) : "memory");
}
__device__ __forceinline__ void tma2d_store(const CUtensorMap* m, uint32_t src, int c0, int c1) {
    asm volatile("cp.async.bulk.tensor.2d.global.shared::cta.bulk_group [%0, {%2, %3}], [%1];"
                 ::"l"((uint64_t)m), "r"(src), "r"(c0), "r"(c1) : "memory");
}
__device__ __forceinline__ void bulk_load(uint32_t dst, const void* src, uint32_t bytes, uint32_t bar) {
    asm volatile("cp.async.bulk.shared::cluster.global.mbarrier::complete_tx::bytes [%0], [%1], %2, [%3];"
                 ::"r"(dst), "l"((uint64_t)src), "r"(bytes), "r"(bar) : "memory");
}
__device__ __forceinline__ void bulk_commit() { asm volatile("cp.async.bulk.commit_group;" ::: "memory"); }
__device__ __forceinline__ void bulk_wait_all() { asm volatile("cp.async.bulk.wait_group 0;" ::: "memory"); }
__device__ __forceinline__ void bulk_wait_read() { asm volatile("cp.async.bulk.wait_group.read 0;" ::: "memory"); }

__device__ __forceinline__ void wgmma_fence() { asm volatile("wgmma.fence.sync.aligned;" ::: "memory"); }
__device__ __forceinline__ void wgmma_commit() { asm volatile("wgmma.commit_group.sync.aligned;" ::: "memory"); }
template <int N>
__device__ __forceinline__ void wgmma_wait() { asm volatile("wgmma.wait_group.sync.aligned %0;" ::"n"(N) : "memory"); }

__device__ __forceinline__ uint64_t mkdesc(uint32_t addr, uint32_t lbo, uint32_t sbo, uint32_t swz) {
    return (uint64_t)((addr & 0x3FFFF) >> 4) | ((uint64_t)(lbo >> 4) << 16) | ((uint64_t)(sbo >> 4) << 32) | ((uint64_t)swz << 62);
}
__device__ __forceinline__ uint32_t pack2(float lo, float hi) {
    uint32_t r;
    asm("cvt.rn.bf16x2.f32 %0, %1, %2;" : "=r"(r) : "f"(hi), "f"(lo));
    return r;
}
__device__ __forceinline__ float bf_lo(uint32_t v) { return __uint_as_float(v << 16); }
__device__ __forceinline__ float bf_hi(uint32_t v) { return __uint_as_float(v & 0xFFFF0000u); }
__device__ __forceinline__ void stmatrix4(uint32_t addr, uint32_t r0, uint32_t r1, uint32_t r2, uint32_t r3) {
    asm volatile("stmatrix.sync.aligned.m8n8.x4.shared.b16 [%0], {%1, %2, %3, %4};" ::"r"(addr), "r"(r0), "r"(r1), "r"(r2), "r"(r3) : "memory");
}
__device__ __forceinline__ uint4 lds128(uint32_t addr) {
    uint4 v;
    asm volatile("ld.shared.v4.u32 {%0, %1, %2, %3}, [%4];" : "=r"(v.x), "=r"(v.y), "=r"(v.z), "=r"(v.w) : "r"(addr) : "memory");
    return v;
}
__device__ __forceinline__ void sts128(uint32_t addr, uint4 v) {
    asm volatile("st.shared.v4.u32 [%0], {%1, %2, %3, %4};" ::"r"(addr), "r"(v.x), "r"(v.y), "r"(v.z), "r"(v.w) : "memory");
}
__device__ __forceinline__ void sts32(uint32_t addr, uint32_t v) {
    asm volatile("st.shared.u32 [%0], %1;" ::"r"(addr), "r"(v) : "memory");
}
__device__ __forceinline__ float ex2(float x) {
    float r;
    asm("ex2.approx.ftz.f32 %0, %1;" : "=f"(r) : "f"(x));
    return r;
}
__device__ __forceinline__ float tanh_fast(float x) {
    float r;
    asm("tanh.approx.f32 %0, %1;" : "=f"(r) : "f"(x));
    return r;
}
__device__ __forceinline__ float gelu_tanh(float u) {
    float z = 0.7978845608028654f * (u + 0.044715f * u * u * u);
    float hu = 0.5f * u;
    return fmaf(hu, tanh_fast(z), hu);
}

template <int N>
__device__ __forceinline__ void zero(float (&a)[N]) {
#pragma unroll
    for (int i = 0; i < N; i++) a[i] = 0.f;
}

template <int TA, int TB>
__device__ __forceinline__ void wgmma_n192(float (&d)[96], uint64_t da, uint64_t db, int scale_d) {
    asm volatile("{\n.reg .pred p;\nsetp.ne.b32 p, %98, 0;\n"
        "wgmma.mma_async.sync.aligned.m64n192k16.f32.bf16.bf16 {%0, %1, %2, %3, %4, %5, %6, %7, %8, %9, %10, %11, %12, %13, %14, %15, %16, %17, %18, %19, %20, %21, %22, %23, %24, %25, %26, %27, %28, %29, %30, %31, %32, %33, %34, %35, %36, %37, %38, %39, %40, %41, %42, %43, %44, %45, %46, %47, %48, %49, %50, %51, %52, %53, %54, %55, %56, %57, %58, %59, %60, %61, %62, %63, %64, %65, %66, %67, %68, %69, %70, %71, %72, %73, %74, %75, %76, %77, %78, %79, %80, %81, %82, %83, %84, %85, %86, %87, %88, %89, %90, %91, %92, %93, %94, %95}, %96, %97, p, 1, 1, %99, %100;\n}\n"
        : "+f"(d[0]), "+f"(d[1]), "+f"(d[2]), "+f"(d[3]), "+f"(d[4]), "+f"(d[5]), "+f"(d[6]), "+f"(d[7]), "+f"(d[8]), "+f"(d[9]), "+f"(d[10]), "+f"(d[11]), "+f"(d[12]), "+f"(d[13]), "+f"(d[14]), "+f"(d[15]), "+f"(d[16]), "+f"(d[17]), "+f"(d[18]), "+f"(d[19]), "+f"(d[20]), "+f"(d[21]), "+f"(d[22]), "+f"(d[23]), "+f"(d[24]), "+f"(d[25]), "+f"(d[26]), "+f"(d[27]), "+f"(d[28]), "+f"(d[29]), "+f"(d[30]), "+f"(d[31]), "+f"(d[32]), "+f"(d[33]), "+f"(d[34]), "+f"(d[35]), "+f"(d[36]), "+f"(d[37]), "+f"(d[38]), "+f"(d[39]), "+f"(d[40]), "+f"(d[41]), "+f"(d[42]), "+f"(d[43]), "+f"(d[44]), "+f"(d[45]), "+f"(d[46]), "+f"(d[47]), "+f"(d[48]), "+f"(d[49]), "+f"(d[50]), "+f"(d[51]), "+f"(d[52]), "+f"(d[53]), "+f"(d[54]), "+f"(d[55]), "+f"(d[56]), "+f"(d[57]), "+f"(d[58]), "+f"(d[59]), "+f"(d[60]), "+f"(d[61]), "+f"(d[62]), "+f"(d[63]), "+f"(d[64]), "+f"(d[65]), "+f"(d[66]), "+f"(d[67]), "+f"(d[68]), "+f"(d[69]), "+f"(d[70]), "+f"(d[71]), "+f"(d[72]), "+f"(d[73]), "+f"(d[74]), "+f"(d[75]), "+f"(d[76]), "+f"(d[77]), "+f"(d[78]), "+f"(d[79]), "+f"(d[80]), "+f"(d[81]), "+f"(d[82]), "+f"(d[83]), "+f"(d[84]), "+f"(d[85]), "+f"(d[86]), "+f"(d[87]), "+f"(d[88]), "+f"(d[89]), "+f"(d[90]), "+f"(d[91]), "+f"(d[92]), "+f"(d[93]), "+f"(d[94]), "+f"(d[95])
        : "l"(da), "l"(db), "r"(scale_d), "n"(TA), "n"(TB));
}
template <int TA, int TB>
__device__ __forceinline__ void wgmma_n224(float (&d)[112], uint64_t da, uint64_t db, int scale_d) {
    asm volatile("{\n.reg .pred p;\nsetp.ne.b32 p, %114, 0;\n"
        "wgmma.mma_async.sync.aligned.m64n224k16.f32.bf16.bf16 {%0, %1, %2, %3, %4, %5, %6, %7, %8, %9, %10, %11, %12, %13, %14, %15, %16, %17, %18, %19, %20, %21, %22, %23, %24, %25, %26, %27, %28, %29, %30, %31, %32, %33, %34, %35, %36, %37, %38, %39, %40, %41, %42, %43, %44, %45, %46, %47, %48, %49, %50, %51, %52, %53, %54, %55, %56, %57, %58, %59, %60, %61, %62, %63, %64, %65, %66, %67, %68, %69, %70, %71, %72, %73, %74, %75, %76, %77, %78, %79, %80, %81, %82, %83, %84, %85, %86, %87, %88, %89, %90, %91, %92, %93, %94, %95, %96, %97, %98, %99, %100, %101, %102, %103, %104, %105, %106, %107, %108, %109, %110, %111}, %112, %113, p, 1, 1, %115, %116;\n}\n"
        : "+f"(d[0]), "+f"(d[1]), "+f"(d[2]), "+f"(d[3]), "+f"(d[4]), "+f"(d[5]), "+f"(d[6]), "+f"(d[7]), "+f"(d[8]), "+f"(d[9]), "+f"(d[10]), "+f"(d[11]), "+f"(d[12]), "+f"(d[13]), "+f"(d[14]), "+f"(d[15]), "+f"(d[16]), "+f"(d[17]), "+f"(d[18]), "+f"(d[19]), "+f"(d[20]), "+f"(d[21]), "+f"(d[22]), "+f"(d[23]), "+f"(d[24]), "+f"(d[25]), "+f"(d[26]), "+f"(d[27]), "+f"(d[28]), "+f"(d[29]), "+f"(d[30]), "+f"(d[31]), "+f"(d[32]), "+f"(d[33]), "+f"(d[34]), "+f"(d[35]), "+f"(d[36]), "+f"(d[37]), "+f"(d[38]), "+f"(d[39]), "+f"(d[40]), "+f"(d[41]), "+f"(d[42]), "+f"(d[43]), "+f"(d[44]), "+f"(d[45]), "+f"(d[46]), "+f"(d[47]), "+f"(d[48]), "+f"(d[49]), "+f"(d[50]), "+f"(d[51]), "+f"(d[52]), "+f"(d[53]), "+f"(d[54]), "+f"(d[55]), "+f"(d[56]), "+f"(d[57]), "+f"(d[58]), "+f"(d[59]), "+f"(d[60]), "+f"(d[61]), "+f"(d[62]), "+f"(d[63]), "+f"(d[64]), "+f"(d[65]), "+f"(d[66]), "+f"(d[67]), "+f"(d[68]), "+f"(d[69]), "+f"(d[70]), "+f"(d[71]), "+f"(d[72]), "+f"(d[73]), "+f"(d[74]), "+f"(d[75]), "+f"(d[76]), "+f"(d[77]), "+f"(d[78]), "+f"(d[79]), "+f"(d[80]), "+f"(d[81]), "+f"(d[82]), "+f"(d[83]), "+f"(d[84]), "+f"(d[85]), "+f"(d[86]), "+f"(d[87]), "+f"(d[88]), "+f"(d[89]), "+f"(d[90]), "+f"(d[91]), "+f"(d[92]), "+f"(d[93]), "+f"(d[94]), "+f"(d[95]), "+f"(d[96]), "+f"(d[97]), "+f"(d[98]), "+f"(d[99]), "+f"(d[100]), "+f"(d[101]), "+f"(d[102]), "+f"(d[103]), "+f"(d[104]), "+f"(d[105]), "+f"(d[106]), "+f"(d[107]), "+f"(d[108]), "+f"(d[109]), "+f"(d[110]), "+f"(d[111])
        : "l"(da), "l"(db), "r"(scale_d), "n"(TA), "n"(TB));
}
template <int TA, int TB>
__device__ __forceinline__ void wgmma_n256(float (&d)[128], uint64_t da, uint64_t db, int scale_d) {
    asm volatile("{\n.reg .pred p;\nsetp.ne.b32 p, %130, 0;\n"
        "wgmma.mma_async.sync.aligned.m64n256k16.f32.bf16.bf16 {%0, %1, %2, %3, %4, %5, %6, %7, %8, %9, %10, %11, %12, %13, %14, %15, %16, %17, %18, %19, %20, %21, %22, %23, %24, %25, %26, %27, %28, %29, %30, %31, %32, %33, %34, %35, %36, %37, %38, %39, %40, %41, %42, %43, %44, %45, %46, %47, %48, %49, %50, %51, %52, %53, %54, %55, %56, %57, %58, %59, %60, %61, %62, %63, %64, %65, %66, %67, %68, %69, %70, %71, %72, %73, %74, %75, %76, %77, %78, %79, %80, %81, %82, %83, %84, %85, %86, %87, %88, %89, %90, %91, %92, %93, %94, %95, %96, %97, %98, %99, %100, %101, %102, %103, %104, %105, %106, %107, %108, %109, %110, %111, %112, %113, %114, %115, %116, %117, %118, %119, %120, %121, %122, %123, %124, %125, %126, %127}, %128, %129, p, 1, 1, %131, %132;\n}\n"
        : "+f"(d[0]), "+f"(d[1]), "+f"(d[2]), "+f"(d[3]), "+f"(d[4]), "+f"(d[5]), "+f"(d[6]), "+f"(d[7]), "+f"(d[8]), "+f"(d[9]), "+f"(d[10]), "+f"(d[11]), "+f"(d[12]), "+f"(d[13]), "+f"(d[14]), "+f"(d[15]), "+f"(d[16]), "+f"(d[17]), "+f"(d[18]), "+f"(d[19]), "+f"(d[20]), "+f"(d[21]), "+f"(d[22]), "+f"(d[23]), "+f"(d[24]), "+f"(d[25]), "+f"(d[26]), "+f"(d[27]), "+f"(d[28]), "+f"(d[29]), "+f"(d[30]), "+f"(d[31]), "+f"(d[32]), "+f"(d[33]), "+f"(d[34]), "+f"(d[35]), "+f"(d[36]), "+f"(d[37]), "+f"(d[38]), "+f"(d[39]), "+f"(d[40]), "+f"(d[41]), "+f"(d[42]), "+f"(d[43]), "+f"(d[44]), "+f"(d[45]), "+f"(d[46]), "+f"(d[47]), "+f"(d[48]), "+f"(d[49]), "+f"(d[50]), "+f"(d[51]), "+f"(d[52]), "+f"(d[53]), "+f"(d[54]), "+f"(d[55]), "+f"(d[56]), "+f"(d[57]), "+f"(d[58]), "+f"(d[59]), "+f"(d[60]), "+f"(d[61]), "+f"(d[62]), "+f"(d[63]), "+f"(d[64]), "+f"(d[65]), "+f"(d[66]), "+f"(d[67]), "+f"(d[68]), "+f"(d[69]), "+f"(d[70]), "+f"(d[71]), "+f"(d[72]), "+f"(d[73]), "+f"(d[74]), "+f"(d[75]), "+f"(d[76]), "+f"(d[77]), "+f"(d[78]), "+f"(d[79]), "+f"(d[80]), "+f"(d[81]), "+f"(d[82]), "+f"(d[83]), "+f"(d[84]), "+f"(d[85]), "+f"(d[86]), "+f"(d[87]), "+f"(d[88]), "+f"(d[89]), "+f"(d[90]), "+f"(d[91]), "+f"(d[92]), "+f"(d[93]), "+f"(d[94]), "+f"(d[95]), "+f"(d[96]), "+f"(d[97]), "+f"(d[98]), "+f"(d[99]), "+f"(d[100]), "+f"(d[101]), "+f"(d[102]), "+f"(d[103]), "+f"(d[104]), "+f"(d[105]), "+f"(d[106]), "+f"(d[107]), "+f"(d[108]), "+f"(d[109]), "+f"(d[110]), "+f"(d[111]), "+f"(d[112]), "+f"(d[113]), "+f"(d[114]), "+f"(d[115]), "+f"(d[116]), "+f"(d[117]), "+f"(d[118]), "+f"(d[119]), "+f"(d[120]), "+f"(d[121]), "+f"(d[122]), "+f"(d[123]), "+f"(d[124]), "+f"(d[125]), "+f"(d[126]), "+f"(d[127])
        : "l"(da), "l"(db), "r"(scale_d), "n"(TA), "n"(TB));
}
template <int TA, int TB>
__device__ __forceinline__ void wgmma_n64(float (&d)[32], uint64_t da, uint64_t db, int scale_d) {
    asm volatile("{\n.reg .pred p;\nsetp.ne.b32 p, %34, 0;\n"
        "wgmma.mma_async.sync.aligned.m64n64k16.f32.bf16.bf16 {%0, %1, %2, %3, %4, %5, %6, %7, %8, %9, %10, %11, %12, %13, %14, %15, %16, %17, %18, %19, %20, %21, %22, %23, %24, %25, %26, %27, %28, %29, %30, %31}, %32, %33, p, 1, 1, %35, %36;\n}\n"
        : "+f"(d[0]), "+f"(d[1]), "+f"(d[2]), "+f"(d[3]), "+f"(d[4]), "+f"(d[5]), "+f"(d[6]), "+f"(d[7]), "+f"(d[8]), "+f"(d[9]), "+f"(d[10]), "+f"(d[11]), "+f"(d[12]), "+f"(d[13]), "+f"(d[14]), "+f"(d[15]), "+f"(d[16]), "+f"(d[17]), "+f"(d[18]), "+f"(d[19]), "+f"(d[20]), "+f"(d[21]), "+f"(d[22]), "+f"(d[23]), "+f"(d[24]), "+f"(d[25]), "+f"(d[26]), "+f"(d[27]), "+f"(d[28]), "+f"(d[29]), "+f"(d[30]), "+f"(d[31])
        : "l"(da), "l"(db), "r"(scale_d), "n"(TA), "n"(TB));
}
template <int TA, int TB>
__device__ __forceinline__ void wgmma_n8(float (&d)[4], uint64_t da, uint64_t db, int scale_d) {
    asm volatile("{\n.reg .pred p;\nsetp.ne.b32 p, %6, 0;\n"
        "wgmma.mma_async.sync.aligned.m64n8k16.f32.bf16.bf16 {%0, %1, %2, %3}, %4, %5, p, 1, 1, %7, %8;\n}\n"
        : "+f"(d[0]), "+f"(d[1]), "+f"(d[2]), "+f"(d[3])
        : "l"(da), "l"(db), "r"(scale_d), "n"(TA), "n"(TB));
}
template <int TB>
__device__ __forceinline__ void wgmma_rs_n40(float (&d)[20], uint32_t a0, uint32_t a1, uint32_t a2, uint32_t a3, uint64_t db, int scale_d) {
    asm volatile("{\n.reg .pred p;\nsetp.ne.b32 p, %25, 0;\n"
        "wgmma.mma_async.sync.aligned.m64n40k16.f32.bf16.bf16 {%0, %1, %2, %3, %4, %5, %6, %7, %8, %9, %10, %11, %12, %13, %14, %15, %16, %17, %18, %19}, {%20, %21, %22, %23}, %24, p, 1, 1, %26;\n}\n"
        : "+f"(d[0]), "+f"(d[1]), "+f"(d[2]), "+f"(d[3]), "+f"(d[4]), "+f"(d[5]), "+f"(d[6]), "+f"(d[7]), "+f"(d[8]), "+f"(d[9]), "+f"(d[10]), "+f"(d[11]), "+f"(d[12]), "+f"(d[13]), "+f"(d[14]), "+f"(d[15]), "+f"(d[16]), "+f"(d[17]), "+f"(d[18]), "+f"(d[19])
        : "r"(a0), "r"(a1), "r"(a2), "r"(a3), "l"(db), "r"(scale_d), "n"(TB));
}

struct Ring {
    uint32_t s, ph;
    __device__ __forceinline__ void next() {
        if (++s == NSTAGE) { s = 0; ph ^= 1; }
    }
};

template <int MODE, int NACC, class Prod>
__device__ __forceinline__ void mainloop(float (&acc)[NACC], int nkb, bool zero_init, Ring& ring, uint32_t sbase, uint32_t bar_full,
                                         uint32_t bar_empty, uint32_t bar_empty_peer, int wg, int lane, Prod& produce) {
    uint32_t prev_s = 0;
    for (int kb = 0; kb < nkb; kb++) {
        const uint32_t slot = sbase + ring.s * SLOT;
        mbar_wait<0>(bar_full + 8 * ring.s, ring.ph);
        wgmma_fence();
#pragma unroll
        for (int j = 0; j < 4; j++) {
            const int sc = (zero_init && kb == 0 && j == 0) ? 0 : 1;
            if constexpr (MODE == 0) {
                uint64_t da = mkdesc(slot + wg * 8192 + j * 32, 16, 1024, 1);
                uint64_t db = mkdesc(slot + 16384 + (j >> 1) * 12288 + (j & 1) * 2048, 4096, 1024, 1);
                wgmma_n192<0, 1>(acc, da, db, sc);
            } else if constexpr (MODE == 1) {
                uint64_t da = mkdesc(slot + wg * 8192 + j * 2048, 8192, 1024, 1);
                uint64_t db = mkdesc(slot + 16384 + (j >> 1) * 14336 + (j & 1) * 1024, 2048, 512, 2);
                wgmma_n224<1, 1>(acc, da, db, sc);
            } else if constexpr (MODE == 2) {
                uint64_t da = mkdesc(slot + wg * 8192 + j * 2048, 8192, 1024, 1);
                uint64_t db = mkdesc(slot + 16384 + j * 32, 16, 1024, 1);
                wgmma_n256<1, 0>(acc, da, db, sc);
            } else {
                uint64_t da = mkdesc(slot + wg * 8192 + j * 32, 16, 1024, 1);
                uint64_t db = mkdesc(slot + 16384 + (j >> 1) * 16384 + (j & 1) * 2048, 4096, 1024, 1);
                wgmma_n256<0, 1>(acc, da, db, sc);
            }
        }
        wgmma_commit();
        if (kb > 0) {
            wgmma_wait<1>();
            if (lane == 0) mbar_arrive(bar_empty + 8 * prev_s);
            else if (lane == 1) mbar_arrive_cluster(bar_empty_peer + 8 * prev_s);
            produce();
        }
        prev_s = ring.s;
        ring.next();
    }
    wgmma_wait<0>();
    if (lane == 0) mbar_arrive(bar_empty + 8 * prev_s);
    else if (lane == 1) mbar_arrive_cluster(bar_empty_peer + 8 * prev_s);
    produce();
}

__device__ __forceinline__ void dual_softmax(const float (&v)[8], uint32_t (&P)[4], uint32_t (&M)[4]) {
    constexpr float L2E = 1.4426950408889634f;
    float mx = fmaxf(fmaxf(fmaxf(v[0], v[1]), fmaxf(v[2], v[3])), fmaxf(fmaxf(v[4], v[5]), fmaxf(v[6], v[7])));
    float mn = fminf(fminf(fminf(v[0], v[1]), fminf(v[2], v[3])), fminf(fminf(v[4], v[5]), fminf(v[6], v[7])));
    mx = fmaxf(mx, __shfl_xor_sync(0xffffffffu, mx, 1));
    mn = fminf(mn, __shfl_xor_sync(0xffffffffu, mn, 1));
    mx = fmaxf(mx, __shfl_xor_sync(0xffffffffu, mx, 2));
    mn = fminf(mn, __shfl_xor_sync(0xffffffffu, mn, 2));
    float ep[8], em[8];
    float sp = 0.f, sm = 0.f;
    const float mxs = mx * L2E, mns = mn * L2E;
#pragma unroll
    for (int i = 0; i < 8; i++) {
        ep[i] = ex2(fmaf(v[i], L2E, -mxs));
        em[i] = ex2(fmaf(v[i], -L2E, mns));
        sp += ep[i];
        sm += em[i];
    }
    sp += __shfl_xor_sync(0xffffffffu, sp, 1);
    sm += __shfl_xor_sync(0xffffffffu, sm, 1);
    sp += __shfl_xor_sync(0xffffffffu, sp, 2);
    sm += __shfl_xor_sync(0xffffffffu, sm, 2);
    const float rp = __frcp_rn(sp), rm = __frcp_rn(sm);
#pragma unroll
    for (int i = 0; i < 4; i++) {
        P[i] = pack2(ep[2 * i] * rp, ep[2 * i + 1] * rp);
        M[i] = pack2(em[2 * i] * rm, em[2 * i + 1] * rm);
    }
}

template <int ROLE>
__device__ __forceinline__ void teardown() {
    __syncwarp();
    if (ROLE == 0) asm volatile("barrier.cluster.arrive.release;\nbarrier.cluster.wait.acquire; // consumer" ::: "memory");
    else asm volatile("barrier.cluster.arrive.release;\nbarrier.cluster.wait.acquire; // side" ::: "memory");
    if (ROLE == 0 && threadIdx.x == 0) {
        unsigned old = atomicAdd(&g_flags[FL_EXIT * 32], 1u);
        if (old == NCTA - 1) {
            for (int i = 0; i < FL_COUNT; i++) g_flags[i * 32] = 0;
        }
    }
}

struct Params {
    const __nv_bfloat16* x;
    const __nv_bfloat16* wphi;
    const __nv_bfloat16* b1;
    const __nv_bfloat16* b2;
    const __nv_bfloat16* gate_w;
};

__global__ void __launch_bounds__(NTHREADS, 1)
fused_kernel(const __grid_constant__ CUtensorMap m_x, const __grid_constant__ CUtensorMap m_wqkv,
             const __grid_constant__ CUtensorMap m_h, const __grid_constant__ CUtensorMap m_w1,
             const __grid_constant__ CUtensorMap m_w2, const __grid_constant__ CUtensorMap m_u,
             const __grid_constant__ CUtensorMap m_o, const __grid_constant__ CUtensorMap m_wo,
             const __grid_constant__ CUtensorMap m_out, const Params prm) {
    extern __shared__ uint8_t smem_raw[];
    const uint32_t sbase = (smem_u32(smem_raw) + 1023u) & ~1023u;
    const uint32_t bar_full = sbase + OFF_BAR;
    const uint32_t bar_empty = bar_full + 8 * NSTAGE;
    const uint32_t bar_stg_full = bar_empty + 8 * NSTAGE;
    const uint32_t bar_stg_empty = bar_stg_full + 8;
    const uint32_t bar_part = bar_stg_empty + 8;
    const uint32_t stg = sbase + OFF_STG;

    const int tid = threadIdx.x;
    const int warp = tid >> 5, lane = tid & 31;
    const int cta = blockIdx.x;
    const int r = cta & 1, p = cta >> 1;
    const int hp = p & 15, tg = p >> 4;
    const int tok_a = tg * 4 + r, tok_b = tg * 4 + 2 + r;
    const int ft = p & 15, dt = (p >> 4) * 2 + r;
    const int st = (p & 7) * 2 + r, nt = (p >> 3) & 3, kh = p >> 5;

    if (tid == 0) {
        for (int i = 0; i < NSTAGE; i++) {
            mbar_init(bar_full + 8 * i, 1);
            mbar_init(bar_empty + 8 * i, 16);
        }
        mbar_init(bar_stg_full, 8);
        mbar_init(bar_stg_empty, 1);
        mbar_init(bar_part, 1);
        asm volatile("fence.mbarrier_init.release.cluster;" ::: "memory");
    }
    __syncthreads();
    asm volatile("barrier.cluster.arrive.release.aligned;\nbarrier.cluster.wait.acquire.aligned;" ::: "memory");

    if (warp >= 8) {
        asm volatile("setmaxnreg.dec.sync.aligned.u32 152;");
        const int et = tid - 256, ew = warp - 8;
        const int g8 = lane >> 2, t4 = lane & 3;
        {
            uint4 v[4][4], gw[4];
            const int row0 = cta * 16 + ew * 4;
#pragma unroll
            for (int i = 0; i < 4; i++)
#pragma unroll
                for (int c = 0; c < 4; c++)
                    v[i][c] = __ldg((const uint4*)(prm.x + (size_t)(row0 + i) * D_ + (c * 32 + lane) * 8));
#pragma unroll
            for (int c = 0; c < 4; c++) gw[c] = __ldg((const uint4*)(prm.gate_w + (c * 32 + lane) * 8));
#pragma unroll
            for (int i = 0; i < 4; i++) {
                float sum = 0.f, dot = 0.f;
#pragma unroll
                for (int c = 0; c < 4; c++) {
                    const uint32_t w[4] = {v[i][c].x, v[i][c].y, v[i][c].z, v[i][c].w};
                    const uint32_t q[4] = {gw[c].x, gw[c].y, gw[c].z, gw[c].w};
#pragma unroll
                    for (int k = 0; k < 4; k++) {
                        sum += bf_lo(w[k]) + bf_hi(w[k]);
                        dot = fmaf(bf_lo(w[k]), bf_lo(q[k]), dot);
                        dot = fmaf(bf_hi(w[k]), bf_hi(q[k]), dot);
                    }
                }
#pragma unroll
                for (int o = 16; o > 0; o >>= 1) {
                    sum += __shfl_xor_sync(0xffffffffu, sum, o);
                    dot += __shfl_xor_sync(0xffffffffu, dot, o);
                }
                const float mean = sum * (1.f / D_);
                float var = 0.f;
#pragma unroll
                for (int c = 0; c < 4; c++) {
                    const uint32_t w[4] = {v[i][c].x, v[i][c].y, v[i][c].z, v[i][c].w};
#pragma unroll
                    for (int k = 0; k < 4; k++) {
                        float a = bf_lo(w[k]) - mean, b = bf_hi(w[k]) - mean;
                        var = fmaf(a, a, var);
                        var = fmaf(b, b, var);
                    }
                }
#pragma unroll
                for (int o = 16; o > 0; o >>= 1) var += __shfl_xor_sync(0xffffffffu, var, o);
                const float rstd = rsqrtf(var * (1.f / D_) + 1e-5f);
#pragma unroll
                for (int c = 0; c < 4; c++) {
                    const uint32_t w[4] = {v[i][c].x, v[i][c].y, v[i][c].z, v[i][c].w};
                    uint4 o;
                    o.x = pack2((bf_lo(w[0]) - mean) * rstd, (bf_hi(w[0]) - mean) * rstd);
                    o.y = pack2((bf_lo(w[1]) - mean) * rstd, (bf_hi(w[1]) - mean) * rstd);
                    o.z = pack2((bf_lo(w[2]) - mean) * rstd, (bf_hi(w[2]) - mean) * rstd);
                    o.w = pack2((bf_lo(w[3]) - mean) * rstd, (bf_hi(w[3]) - mean) * rstd);
                    *(uint4*)(g_h + (size_t)(row0 + i) * D_ + (c * 32 + lane) * 8) = o;
                }
                if (lane == 0) g_gate[row0 + i] = 1.f / (1.f + __expf(-dot));
            }
            fence_async_all();
            bar_sync(1, 128);
            if (et == 0) flag_add(&g_flags[FL_LN * 32]);
        }
        {
#pragma unroll
            for (int i = 0; i < 4; i++) {
                const int idx = i * 128 + et, k = idx >> 3, u = idx & 7;
                uint4 val = make_uint4(0, 0, 0, 0);
                if ((k >> 5) == (u >> 2))
                    val = __ldg((const uint4*)(prm.wphi + ((size_t)(hp * 2 + (k >> 5)) * 32 + (k & 31)) * 32 + (u & 3) * 8));
                sts128(sbase + OFF_WPHI + k * 128 + ((u ^ (k & 7)) << 4), val);
            }
            if (et < 64) sts128(sbase + OFF_ONES + et * 16, make_uint4(0x3F803F80u, 0x3F803F80u, 0x3F803F80u, 0x3F803F80u));
            if (et < 28) sts128(sbase + OFF_BIAS + et * 16, __ldg((const uint4*)(prm.b1 + ft * 224 + et * 8)));
            fence_async_smem();
            bar_sync(1, 128);
        }
        const int mrow = (lane >> 3 & 1) * 8 + (lane & 7);
        const int mblk = lane >> 4;
        const uint64_t d_ones = mkdesc(sbase + OFF_ONES, 128, 128, 0);

        auto qkv_epilogue = [&](int tile, uint32_t parity) {
            mbar_wait<1>(bar_stg_full, parity);
#pragma unroll
            for (int mb = 0; mb < 2; mb++) {
                float pa[32];
                zero(pa);
                wgmma_fence();
#pragma unroll
                for (int j = 0; j < 4; j++)
                    wgmma_n64<0, 1>(pa, mkdesc(stg + mb * 8192 + j * 32, 16, 1024, 1), mkdesc(sbase + OFF_WPHI + j * 2048, 4096, 1024, 1), j > 0);
                wgmma_commit();
                wgmma_wait<0>();
                uint4* dst = &g_pq[(size_t)(((cta * 2 + tile) * 2 + mb) * 4) * 128 + et];
#pragma unroll
                for (int i = 0; i < 4; i++)
                    dst[i * 128] = make_uint4(pack2(pa[8 * i], pa[8 * i + 1]), pack2(pa[8 * i + 2], pa[8 * i + 3]),
                                              pack2(pa[8 * i + 4], pa[8 * i + 5]), pack2(pa[8 * i + 6], pa[8 * i + 7]));
            }
#pragma unroll
            for (int mb = 0; mb < 2; mb++) {
                float pa[32];
                zero(pa);
                wgmma_fence();
#pragma unroll
                for (int j = 0; j < 4; j++)
                    wgmma_n64<0, 1>(pa, mkdesc(stg + 16384 + mb * 8192 + j * 32, 16, 1024, 1), mkdesc(sbase + OFF_WPHI + j * 2048, 4096, 1024, 1), j > 0);
                wgmma_commit();
                wgmma_wait<0>();
                bar_sync(1, 128);
                const int row = mb * 64 + ew * 16 + mrow;
#pragma unroll
                for (int hh = 0; hh < 2; hh++) {
                    float v0[8], v1[8];
#pragma unroll
                    for (int b = 0; b < 4; b++) {
                        uint32_t a = pack2(pa[16 * hh + 4 * b], pa[16 * hh + 4 * b + 1]);
                        uint32_t c = pack2(pa[16 * hh + 4 * b + 2], pa[16 * hh + 4 * b + 3]);
                        v0[2 * b] = bf_lo(a); v0[2 * b + 1] = bf_hi(a);
                        v1[2 * b] = bf_lo(c); v1[2 * b + 1] = bf_hi(c);
                    }
                    uint32_t P0[4], M0[4], P1[4], M1[4];
                    dual_softmax(v0, P0, M0);
                    dual_softmax(v1, P1, M1);
                    const uint32_t base = stg + hh * 16384 + row * 128;
                    const int sw = row & 7;
                    stmatrix4(base + (((0 + mblk) ^ sw) << 4), P0[0], P1[0], P0[1], P1[1]);
                    stmatrix4(base + (((2 + mblk) ^ sw) << 4), P0[2], P1[2], P0[3], P1[3]);
                    stmatrix4(base + (((4 + mblk) ^ sw) << 4), M0[0], M1[0], M0[1], M1[1]);
                    stmatrix4(base + (((6 + mblk) ^ sw) << 4), M0[2], M1[2], M0[3], M1[3]);
                }
            }
            fence_async_smem();
            bar_sync(1, 128);
#pragma unroll
            for (int hh = 0; hh < 2; hh++) {
                float kv[32], zz[4];
                zero(kv); zero(zz);
                wgmma_fence();
#pragma unroll
                for (int ks = 0; ks < 8; ks++) {
                    const uint64_t da = mkdesc(stg + hh * 16384 + ks * 2048, 8192, 1024, 1);
                    wgmma_n64<1, 1>(kv, da, mkdesc(stg + 32768 + ks * 2048, 4096, 1024, 1), ks > 0);
                    wgmma_n8<1, 0>(zz, da, d_ones, ks > 0);
                }
                wgmma_commit();
                wgmma_wait<0>();
                float4* dst = &g_kvpart[(size_t)((cta * 2 + hh) * 5) * 128 + et];
#pragma unroll
                for (int i = 0; i < 5; i++) {
                    float4 val = (i < 4) ? make_float4(kv[16 * hh + 4 * (i & 3)], kv[16 * hh + 4 * (i & 3) + 1], kv[16 * hh + 4 * (i & 3) + 2], kv[16 * hh + 4 * (i & 3) + 3])
                                         : make_float4(zz[0], zz[2], 0.f, 0.f);
                    if (tile) {
                        float4 o = dst[i * 128];
                        val.x += o.x; val.y += o.y; val.z += o.z; val.w += o.w;
                    }
                    dst[i * 128] = val;
                }
            }
            bar_sync(1, 128);
        };

        qkv_epilogue(0, 0);
        if (et == 0) mbar_arrive(bar_stg_empty);

        {
            mbar_wait<1>(bar_stg_full, 1);
#pragma unroll 4
            for (int it = 0; it < 28; it++) {
                const int idx = it * 128 + et;
                const int row = idx / 28, u = idx - row * 28;
                const uint4 a = lds128(stg + row * STG_PITCH + u * 16);
                const uint4 b = lds128(sbase + OFF_BIAS + u * 16);
                const uint32_t av[4] = {a.x, a.y, a.z, a.w}, bv[4] = {b.x, b.y, b.z, b.w};
                uint32_t ov[4];
#pragma unroll
                for (int k = 0; k < 4; k++) {
                    uint32_t tsum = pack2(bf_lo(av[k]) + bf_lo(bv[k]), bf_hi(av[k]) + bf_hi(bv[k]));
                    ov[k] = pack2(gelu_tanh(bf_lo(tsum)), gelu_tanh(bf_hi(tsum)));
                }
                *(uint4*)(g_u + (size_t)(dt * 128 + row) * F_ + ft * 224 + u * 8) = make_uint4(ov[0], ov[1], ov[2], ov[3]);
            }
            fence_async_all();
            bar_sync(1, 128);
            if (et == 0) {
                mbar_arrive(bar_stg_empty);
                flag_add(&g_flags[(FL_U + (dt >> 1)) * 32]);
            }
        }

        qkv_epilogue(1, 0);
        if (et == 0) {
            flag_add(&g_flags[(FL_KV + hp) * 32]);
            wait_flag<1>(&g_flags[(FL_KV + hp) * 32], 8);
        }
        bar_sync(1, 128);

        {
            const int f0 = ew * 16 + g8, f1 = f0 + 8;
#pragma unroll
            for (int hh = 0; hh < 2; hh++) {
                float4 s[5];
#pragma unroll
                for (int i = 0; i < 5; i++) s[i] = make_float4(0.f, 0.f, 0.f, 0.f);
#pragma unroll
                for (int c = 0; c < 8; c++) {
                    const int oc = ((c >> 1) * 16 + hp) * 2 + (c & 1);
                    const float4* src = &g_kvpart[(size_t)((oc * 2 + hh) * 5) * 128 + et];
#pragma unroll
                    for (int i = 0; i < 5; i++) {
                        float4 o = __ldcg(src + i * 128);
                        s[i].x += o.x; s[i].y += o.y; s[i].z += o.z; s[i].w += o.w;
                    }
                }
                const uint32_t base = stg + 32768 + hh * 8192 + t4 * 4;
#pragma unroll
                for (int i = 0; i < 4; i++) {
                    sts32(base + f0 * 128 + ((i ^ (f0 & 7)) << 4), pack2(s[i].x, s[i].y));
                    sts32(base + f1 * 128 + ((i ^ (f1 & 7)) << 4), pack2(s[i].z, s[i].w));
                }
                sts32(base + f0 * 128 + ((4 ^ (f0 & 7)) << 4), pack2(s[4].x, s[4].x));
                sts32(base + f1 * 128 + ((4 ^ (f1 & 7)) << 4), pack2(s[4].y, s[4].y));
            }
            fence_async_smem();
            bar_sync(1, 128);
        }
#pragma unroll 1
        for (int tile = 0; tile < 2; tile++) {
            const int tok = tile ? tok_b : tok_a;
#pragma unroll 1
            for (int mb = 0; mb < 2; mb++) {
                const uint4* src = &g_pq[(size_t)(((cta * 2 + tile) * 2 + mb) * 4) * 128 + et];
                uint4 q[4];
#pragma unroll
                for (int i = 0; i < 4; i++) q[i] = src[i * 128];
                const int grow = tok * 128 + mb * 64 + ew * 16 + g8;
                const float gt0 = __ldcg(&g_gate[grow]), gt1 = __ldcg(&g_gate[grow + 8]);
                const int row = mb * 64 + ew * 16 + mrow;
                const int sw = row & 7;
#pragma unroll
                for (int hh = 0; hh < 2; hh++) {
                    float v0[8], v1[8];
                    v0[0] = bf_lo(q[2 * hh].x); v0[1] = bf_hi(q[2 * hh].x); v1[0] = bf_lo(q[2 * hh].y); v1[1] = bf_hi(q[2 * hh].y);
                    v0[2] = bf_lo(q[2 * hh].z); v0[3] = bf_hi(q[2 * hh].z); v1[2] = bf_lo(q[2 * hh].w); v1[3] = bf_hi(q[2 * hh].w);
                    v0[4] = bf_lo(q[2 * hh + 1].x); v0[5] = bf_hi(q[2 * hh + 1].x); v1[4] = bf_lo(q[2 * hh + 1].y); v1[5] = bf_hi(q[2 * hh + 1].y);
                    v0[6] = bf_lo(q[2 * hh + 1].z); v0[7] = bf_hi(q[2 * hh + 1].z); v1[6] = bf_lo(q[2 * hh + 1].w); v1[7] = bf_hi(q[2 * hh + 1].w);
                    uint32_t P0[4], M0[4], P1[4], M1[4];
                    dual_softmax(v0, P0, M0);
                    dual_softmax(v1, P1, M1);
                    float o[20];
                    zero(o);
                    const uint32_t kb = stg + 32768 + hh * 8192;
                    wgmma_fence();
                    wgmma_rs_n40<1>(o, P0[0], P1[0], P0[1], P1[1], mkdesc(kb, 4096, 1024, 1), 0);
                    wgmma_rs_n40<1>(o, P0[2], P1[2], P0[3], P1[3], mkdesc(kb + 2048, 4096, 1024, 1), 1);
                    wgmma_rs_n40<1>(o, M0[0], M1[0], M0[1], M1[1], mkdesc(kb + 4096, 4096, 1024, 1), 1);
                    wgmma_rs_n40<1>(o, M0[2], M1[2], M0[3], M1[3], mkdesc(kb + 6144, 4096, 1024, 1), 1);
                    wgmma_commit();
                    wgmma_wait<0>();
                    const float s0 = __fdividef(gt0, o[16] + 1e-6f), s1 = __fdividef(gt1, o[18] + 1e-6f);
                    const uint32_t base = stg + tile * 16384 + row * 128;
                    stmatrix4(base + (((hh * 4 + 0 + mblk) ^ sw) << 4), pack2(o[0] * s0, o[1] * s0), pack2(o[2] * s1, o[3] * s1),
                              pack2(o[4] * s0, o[5] * s0), pack2(o[6] * s1, o[7] * s1));
                    stmatrix4(base + (((hh * 4 + 2 + mblk) ^ sw) << 4), pack2(o[8] * s0, o[9] * s0), pack2(o[10] * s1, o[11] * s1),
                              pack2(o[12] * s0, o[13] * s0), pack2(o[14] * s1, o[15] * s1));
                }
            }
            fence_async_smem();
            bar_sync(1, 128);
            if (et == 0) {
                tma2d_store(&m_o, stg + tile * 16384, hp * 64, tok * 128);
                bulk_commit();
            }
        }
        if (et == 0) {
            bulk_wait_all();
            fence_async_all();
            flag_add(&g_flags[(FL_O + tok_a) * 32]);
            flag_add(&g_flags[(FL_O + tok_b) * 32]);
            if (kh) {
                wait_flag<1>(&g_flags[(FL_PART + st * 4 + nt) * 32], 1);
                fence_async_all();
                mbar_expect_tx(bar_part, 65536);
                const uint8_t* src = (const uint8_t*)&g_part[(size_t)(st * 4 + nt) * 16 * 256];
                for (int i = 0; i < 4; i++) bulk_load(stg + i * 16384, src + i * 16384, 16384, bar_part);
            }
        }
        teardown<1>();
    } else {
        asm volatile("setmaxnreg.inc.sync.aligned.u32 176;");
        const int wg = warp >> 2, wq = warp & 3;
        const uint32_t bar_empty_peer = mapa(bar_empty, r ^ 1);
        const int mrow = wg * 64 + wq * 16 + (lane >> 3 & 1) * 8 + (lane & 7);
        const int mblk = lane >> 4;
        Ring ring{0, 0};

        const int nB = kh ? FB - N0 : N0, f0 = kh ? N0 : 0;
        const int total = 64 + nB + (kh ? 16 : 0);
        int pidx = 0;
        Ring pring{0, 1};
        auto produce = [&]() {
            if (tid == 0 && pidx < total) {
                const int i = pidx++;
                const uint32_t slot = sbase + pring.s * SLOT, fb = bar_full + 8 * pring.s;
                if (i == 16) { wait_flag<0>(&g_flags[FL_LN * 32], NCTA); fence_async_all(); }
                else if (i == 64) { wait_flag<0>(&g_flags[(FL_U + nt) * 32], 32); fence_async_all(); }
                else if (i == 64 + nB) { wait_flag<0>(&g_flags[(FL_O + st) * 32], 16); fence_async_all(); }
                mbar_wait<0>(bar_empty + 8 * pring.s, pring.ph);
                if (i < 16 || (i >= 48 && i < 64)) {
                    const int kb = i & 15;
                    mbar_expect_tx(fb, 40960);
                    tma2d(slot, &m_x, kb * 64, (i < 16 ? tok_a : tok_b) * 128, fb);
                    tma3d_mc(slot + 16384 + r * 12288, &m_wqkv, hp * 64, kb * 64 + r * 32, 0, fb);
                } else if (i < 48) {
                    const int kb = i - 16;
                    mbar_expect_tx(fb, 45056);
                    tma3d(slot, &m_h, 0, kb * 64, dt * 2, fb);
                    tma3d_mc(slot + 16384 + r * 14336, &m_w1, 0, kb * 64 + r * 32, ft * 7, fb);
                } else if (i < 64 + nB) {
                    const int kb = f0 + i - 64;
                    mbar_expect_tx(fb, 49152);
                    tma3d(slot, &m_w2, 0, kb * 64, st * 2, fb);
                    tma2d_mc(slot + 16384 + r * 16384, &m_u, kb * 64, nt * 256 + r * 128, fb);
                } else {
                    const int kb = i - 64 - nB;
                    mbar_expect_tx(fb, 49152);
                    tma2d(slot, &m_o, kb * 64, st * 128, fb);
                    tma3d_mc(slot + 16384 + r * 16384, &m_wo, 0, kb * 64 + r * 32, nt * 4, fb);
                }
                pring.next();
            }
            __syncwarp();
        };
#pragma unroll 1
        for (int i = 0; i < NSTAGE; i++) produce();

#pragma unroll 1
        for (int pass = 0; pass < 2; pass++) {
            {
                float acc[96];
                zero(acc);
                mainloop<0>(acc, 16, true, ring, sbase, bar_full, bar_empty, bar_empty_peer, wg, lane, produce);
                if (pass) mbar_wait<0>(bar_stg_empty, 1);
                const uint32_t base = stg + mrow * 128;
                const int sw = mrow & 7;
#pragma unroll
                for (int jb = 0; jb < 12; jb++) {
                    const uint32_t addr = base + (jb >> 2) * 16384 + (((((2 * jb) & 7) + mblk) ^ sw) << 4);
                    stmatrix4(addr, pack2(acc[8 * jb], acc[8 * jb + 1]), pack2(acc[8 * jb + 2], acc[8 * jb + 3]),
                              pack2(acc[8 * jb + 4], acc[8 * jb + 5]), pack2(acc[8 * jb + 6], acc[8 * jb + 7]));
                }
                fence_async_smem();
                __syncwarp();
                if (lane == 0) mbar_arrive(bar_stg_full);
            }
            if (pass == 0) {
                float acc[112];
                zero(acc);
                mainloop<1>(acc, 32, true, ring, sbase, bar_full, bar_empty, bar_empty_peer, wg, lane, produce);
                mbar_wait<0>(bar_stg_empty, 0);
                const uint32_t base = stg + mrow * STG_PITCH + mblk * 16;
#pragma unroll
                for (int jb = 0; jb < 14; jb++)
                    stmatrix4(base + jb * 32, pack2(acc[8 * jb], acc[8 * jb + 1]), pack2(acc[8 * jb + 2], acc[8 * jb + 3]),
                              pack2(acc[8 * jb + 4], acc[8 * jb + 5]), pack2(acc[8 * jb + 6], acc[8 * jb + 7]));
                __syncwarp();
                if (lane == 0) mbar_arrive(bar_stg_full);
            }
        }
        float acc[128];
        zero(acc);
        const int grow = st * 128 + wg * 64 + wq * 16 + (lane >> 2);
        mainloop<2>(acc, nB, true, ring, sbase, bar_full, bar_empty, bar_empty_peer, wg, lane, produce);
        const float c0 = 1.f - __ldcg(&g_gate[grow]), c1 = 1.f - __ldcg(&g_gate[grow + 8]);
        if (kh == 0) {
            uint4* dst = &g_part[(size_t)(st * 4 + nt) * 16 * 256 + tid];
#pragma unroll
            for (int i = 0; i < 16; i++)
                dst[i * 256] = make_uint4(pack2(acc[8 * i] * c0, acc[8 * i + 1] * c0), pack2(acc[8 * i + 2] * c1, acc[8 * i + 3] * c1),
                                          pack2(acc[8 * i + 4] * c0, acc[8 * i + 5] * c0), pack2(acc[8 * i + 6] * c1, acc[8 * i + 7] * c1));
            fence_async_all();
            bar_sync(2, 256);
            if (tid == 0) flag_add(&g_flags[(FL_PART + st * 4 + nt) * 32]);
        } else {
            {
                const float b0 = __bfloat162float(prm.b2[grow]), b1v = __bfloat162float(prm.b2[grow + 8]);
#pragma unroll
                for (int i = 0; i < 32; i++) {
                    acc[4 * i] = (acc[4 * i] + b0) * c0;
                    acc[4 * i + 1] = (acc[4 * i + 1] + b0) * c0;
                    acc[4 * i + 2] = (acc[4 * i + 2] + b1v) * c1;
                    acc[4 * i + 3] = (acc[4 * i + 3] + b1v) * c1;
                }
            }
            mainloop<3>(acc, 16, false, ring, sbase, bar_full, bar_empty, bar_empty_peer, wg, lane, produce);
            mbar_wait<0>(bar_part, 0);
            bar_sync(2, 256);
            const int orow = wq * 16 + (lane >> 3 & 1) * 8 + (lane & 7);
            const uint32_t obase = sbase + wg * 32768 + orow * 128;
            const int sw = orow & 7;
#pragma unroll
            for (int i = 0; i < 16; i++) {
                const uint4 pv = lds128(stg + (i * 256 + tid) * 16);
                const uint32_t addr = obase + (i >> 2) * 8192 + (((((2 * i) & 7) + mblk) ^ sw) << 4);
                stmatrix4(addr, pack2(acc[8 * i] + bf_lo(pv.x), acc[8 * i + 1] + bf_hi(pv.x)),
                          pack2(acc[8 * i + 2] + bf_lo(pv.y), acc[8 * i + 3] + bf_hi(pv.y)),
                          pack2(acc[8 * i + 4] + bf_lo(pv.z), acc[8 * i + 5] + bf_hi(pv.z)),
                          pack2(acc[8 * i + 6] + bf_lo(pv.w), acc[8 * i + 7] + bf_hi(pv.w)));
            }
            fence_async_smem();
            bar_sync(3 + wg, 128);
            if ((tid & 127) == 0) {
#pragma unroll
                for (int c = 0; c < 4; c++)
                    tma2d_store(&m_out, sbase + wg * 32768 + c * 8192, nt * 256 + c * 64, st * 128 + wg * 64);
                bulk_commit();
                bulk_wait_read();
            }
        }
        teardown<0>();
    }
}

typedef CUresult (*EncodeFn)(CUtensorMap*, CUtensorMapDataType, cuuint32_t, void*, const cuuint64_t*, const cuuint64_t*,
                             const cuuint32_t*, const cuuint32_t*, CUtensorMapInterleave, CUtensorMapSwizzle,
                             CUtensorMapL2promotion, CUtensorMapFloatOOBfill);

void make_map(EncodeFn enc, CUtensorMap* m, const void* ptr, int rank, const uint64_t* dims, const uint64_t* strides_bytes,
              const uint32_t* box, CUtensorMapSwizzle swz) {
    cuuint64_t gd[3], gs[2];
    cuuint32_t bd[3], es[3] = {1, 1, 1};
    for (int i = 0; i < rank; i++) { gd[i] = dims[i]; bd[i] = box[i]; }
    for (int i = 0; i < rank - 1; i++) gs[i] = strides_bytes[i];
    CUresult res = enc(m, CU_TENSOR_MAP_DATA_TYPE_BFLOAT16, rank, const_cast<void*>(ptr), gd, gs, bd, es, CU_TENSOR_MAP_INTERLEAVE_NONE, swz,
        CU_TENSOR_MAP_L2_PROMOTION_L2_128B, CU_TENSOR_MAP_FLOAT_OOB_FILL_NONE);
    (void)res;
}

}

extern "C" void kernel_launch(void* const* d_in, const int* in_sizes, int n_in, void* d_out, int out_size) {
    (void)in_sizes; (void)n_in; (void)out_size;
    const __nv_bfloat16* x = (const __nv_bfloat16*)d_in[0];
    const __nv_bfloat16* wqkv = (const __nv_bfloat16*)d_in[1];
    const __nv_bfloat16* wphi = (const __nv_bfloat16*)d_in[2];
    const __nv_bfloat16* wo = (const __nv_bfloat16*)d_in[3];
    const __nv_bfloat16* w1 = (const __nv_bfloat16*)d_in[5];
    const __nv_bfloat16* b1 = (const __nv_bfloat16*)d_in[6];
    const __nv_bfloat16* w2 = (const __nv_bfloat16*)d_in[7];
    const __nv_bfloat16* b2 = (const __nv_bfloat16*)d_in[8];
    const __nv_bfloat16* gate_w = (const __nv_bfloat16*)d_in[9];

    EncodeFn enc = nullptr;
    cudaDriverEntryPointQueryResult qr;
    cudaGetDriverEntryPoint("cuTensorMapEncodeTiled", (void**)&enc, cudaEnableDefault, &qr);
    void *p_h, *p_u, *p_o;
    cudaGetSymbolAddress(&p_h, g_h);
    cudaGetSymbolAddress(&p_u, g_u);
    cudaGetSymbolAddress(&p_o, g_o);

    CUtensorMap m_x, m_wqkv, m_h, m_w1, m_w2, m_u, m_o, m_wo, m_out;
    {
        uint64_t d[2] = {1024, 2048}, s[1] = {2048};
        uint32_t b[2] = {64, 128};
        make_map(enc, &m_x, x, 2, d, s, b, CU_TENSOR_MAP_SWIZZLE_128B);
        make_map(enc, &m_o, p_o, 2, d, s, b, CU_TENSOR_MAP_SWIZZLE_128B);
        uint32_t b2_[2] = {64, 64};
        make_map(enc, &m_out, d_out, 2, d, s, b2_, CU_TENSOR_MAP_SWIZZLE_128B);
    }
    {
        uint64_t d[3] = {1024, 1024, 3}, s[2] = {6144, 2048};
        uint32_t b[3] = {64, 32, 3};
        make_map(enc, &m_wqkv, wqkv, 3, d, s, b, CU_TENSOR_MAP_SWIZZLE_128B);
    }
    {
        uint64_t d[3] = {64, 2048, 16}, s[2] = {2048, 128};
        uint32_t b[3] = {64, 64, 2};
        make_map(enc, &m_h, p_h, 3, d, s, b, CU_TENSOR_MAP_SWIZZLE_128B);
    }
    {
        uint64_t d[3] = {32, 2048, 112}, s[2] = {7168, 64};
        uint32_t b[3] = {32, 32, 7};
        make_map(enc, &m_w1, w1, 3, d, s, b, CU_TENSOR_MAP_SWIZZLE_64B);
    }
    {
        uint64_t d[3] = {64, 3584, 32}, s[2] = {4096, 128};
        uint32_t b[3] = {64, 64, 2};
        make_map(enc, &m_w2, w2, 3, d, s, b, CU_TENSOR_MAP_SWIZZLE_128B);
    }
    {
        uint64_t d[2] = {3584, 1024}, s[1] = {7168};
        uint32_t b[2] = {64, 128};
        make_map(enc, &m_u, p_u, 2, d, s, b, CU_TENSOR_MAP_SWIZZLE_128B);
    }
    {
        uint64_t d[3] = {64, 1024, 16}, s[2] = {2048, 128};
        uint32_t b[3] = {64, 32, 4};
        make_map(enc, &m_wo, wo, 3, d, s, b, CU_TENSOR_MAP_SWIZZLE_128B);
    }
    Params prm{x, wphi, b1, b2, gate_w};

    cudaFuncSetAttribute(fused_kernel, cudaFuncAttributeMaxDynamicSharedMemorySize, SMEM_BYTES);
    cudaLaunchConfig_t cfg = {};
    cfg.gridDim = dim3(NCTA);
    cfg.blockDim = dim3(NTHREADS);
    cfg.dynamicSmemBytes = SMEM_BYTES;
    cfg.stream = cudaStreamPerThread;
    cudaLaunchAttribute at[1];
    at[0].id = cudaLaunchAttributeClusterDimension;
    at[0].val.clusterDim.x = 2;
    at[0].val.clusterDim.y = 1;
    at[0].val.clusterDim.z = 1;
    cfg.attrs = at;
    cfg.numAttrs = 1;
    cudaLaunchKernelEx(&cfg, fused_kernel, m_x, m_wqkv, m_h, m_w1, m_w2, m_u, m_o, m_wo, m_out, prm);
}
```

```cpp
#include <cuda_runtime.h>
#include <cuda.h>
#include <cuda_bf16.h>
#include <stdint.h>

namespace {

constexpr int S_ = 2048, D_ = 1024, F_ = 3584;
constexpr int NCTA = 128;
#define BK_ 32
constexpr int BK = BK_;
constexpr int NSTAGE = 192 / BK;
constexpr int SLOT = BK * 768;
constexpr int BOFF = BK * 256;
constexpr int OFF_STG = NSTAGE * SLOT;
constexpr int OFF_WPHI = OFF_STG + 65536;
constexpr int OFF_BAR = OFF_WPHI + 8192;
constexpr int OFF_TAB = OFF_BAR + 256;
constexpr int SMEM_BYTES = OFF_TAB + 512 + 1024;
#define N0_ 26
constexpr int N0 = N0_ * (64 / BK);
constexpr int FB = F_ / BK;
constexpr int NTHREADS = 384;
#define S1_ 14
#define S2_ 19
constexpr int S1 = S1_ * (64 / BK), S2 = S2_ * (64 / BK);

constexpr int FL_LN = 0, FL_U = 1, FL_KV = 5, FL_O = 21, FL_PART = 37, FL_EXIT = 101, FL_COUNT = 102;

__device__ __align__(1024) __nv_bfloat16 g_h[S_ * D_];
__device__ __align__(1024) __nv_bfloat16 g_u[F_ * D_];
__device__ __align__(1024) __nv_bfloat16 g_o[D_ * S_];
__device__ __align__(1024) uint4 g_pq[NCTA * 16 * 8 * 32];
__device__ __align__(1024) float4 g_kvsum[16 * 2 * 8 * 96];
__device__ __align__(1024) uint4 g_part[64 * 16 * 256];
__device__ __align__(1024) float g_gate[S_];
__device__ __align__(1024) unsigned g_flags[FL_COUNT * 32];

#define TL(cond, idx)
#define TR(cond, idx)
#define TLG(cond, idx)
__device__ __forceinline__ uint32_t smem_u32(const void* p) { return (uint32_t)__cvta_generic_to_shared(p); }
__device__ __forceinline__ void mbar_init(uint32_t bar, uint32_t cnt) {
    asm volatile("mbarrier.init.shared::cta.b64 [%0], %1;" ::"r"(bar), "r"(cnt));
}
__device__ __forceinline__ void mbar_expect_tx(uint32_t bar, uint32_t bytes) {
    asm volatile("mbarrier.arrive.expect_tx.shared::cta.b64 _, [%0], %1;" ::"r"(bar), "r"(bytes) : "memory");
}
__device__ __forceinline__ void mbar_arrive(uint32_t bar) {
    asm volatile("mbarrier.arrive.shared::cta.b64 _, [%0];" ::"r"(bar) : "memory");
}
template <int ROLE>
__device__ __forceinline__ void mbar_wait(uint32_t bar, uint32_t parity) {
    uint32_t done;
    int n = 0;
    while (true) {
        asm volatile("{\n.reg .pred p;\nmbarrier.try_wait.parity.shared::cta.b64 p, [%1], %2;\nselp.u32 %0, 1, 0, p;\n}"
                     : "=r"(done) : "r"(bar), "r"(parity) : "memory");
        if (done || ++n >= (1 << 16)) break;
    }
}
__device__ __forceinline__ bool mbar_test(uint32_t bar, uint32_t parity) {
    uint32_t done;
    asm volatile("{\n.reg .pred p;\nmbarrier.test_wait.parity.shared::cta.b64 p, [%1], %2;\nselp.u32 %0, 1, 0, p;\n}"
                 : "=r"(done) : "r"(bar), "r"(parity) : "memory");
    return done != 0;
}
__device__ __forceinline__ bool mbar_try(uint32_t bar, uint32_t parity, uint32_t ns) {
    uint32_t done;
    asm volatile("{\n.reg .pred p;\nmbarrier.try_wait.parity.shared::cta.b64 p, [%1], %2, %3;\nselp.u32 %0, 1, 0, p;\n}"
                 : "=r"(done) : "r"(bar), "r"(parity), "r"(ns) : "memory");
    return done != 0;
}
__device__ __forceinline__ unsigned ld_relaxed(const unsigned* p) {
    unsigned v;
    asm volatile("ld.relaxed.gpu.global.u32 %0, [%1];" : "=r"(v) : "l"(p) : "memory");
    return v;
}
template <int ROLE>
__device__ __forceinline__ void wait_flag(const unsigned* p, unsigned target) {
    unsigned v;
    int n = 0;
    while (true) {
        asm volatile("ld.acquire.gpu.global.u32 %0, [%1];" : "=r"(v) : "l"(p) : "memory");
        if (v >= target) break;
        if (++n > (1 << 16)) {
            break;
        }
        __nanosleep(40);
    }
}
__device__ __forceinline__ void flag_add(unsigned* p) {
    asm volatile("red.release.gpu.global.add.u32 [%0], 1;" ::"l"(p) : "memory");
}
__device__ __forceinline__ void fence_async_smem() { asm volatile("fence.proxy.async.shared::cta;" ::: "memory"); }
__device__ __forceinline__ void fence_async_glob() { asm volatile("fence.proxy.async.global;" ::: "memory"); }
__device__ __forceinline__ void bar_sync(int id, int n) { asm volatile("bar.sync %0, %1;" ::"r"(id), "r"(n) : "memory"); }

__device__ __forceinline__ void tma3d(uint32_t dst, const CUtensorMap* m, int c0, int c1, int c2, uint32_t bar) {
    asm volatile("cp.async.bulk.tensor.3d.shared::cluster.global.mbarrier::complete_tx::bytes [%0], [%1, {%3, %4, %5}], [%2];"
                 ::"r"(dst), "l"((uint64_t)m), "r"(bar), "r"(c0), "r"(c1), "r"(c2) : "memory");
}
__device__ __forceinline__ void tma2d_store(const CUtensorMap* m, uint32_t src, int c0, int c1) {
    asm volatile("cp.async.bulk.tensor.2d.global.shared::cta.bulk_group [%0, {%2, %3}], [%1];"
                 ::"l"((uint64_t)m), "r"(src), "r"(c0), "r"(c1) : "memory");
}
__device__ __forceinline__ void tma3d_store(const CUtensorMap* m, uint32_t src, int c0, int c1, int c2) {
    asm volatile("cp.async.bulk.tensor.3d.global.shared::cta.bulk_group [%0, {%2, %3, %4}], [%1];"
                 ::"l"((uint64_t)m), "r"(src), "r"(c0), "r"(c1), "r"(c2) : "memory");
}
__device__ __forceinline__ void tma3d_prefetch(const CUtensorMap* m, int c0, int c1, int c2) {
    asm volatile("cp.async.bulk.prefetch.tensor.3d.L2.global [%0, {%1, %2, %3}];" ::"l"((uint64_t)m), "r"(c0), "r"(c1), "r"(c2) : "memory");
}
__device__ __forceinline__ void bulk_prefetch_l2(const void* src, uint32_t bytes) {
    asm volatile("cp.async.bulk.prefetch.L2.global [%0], %1;" ::"l"((uint64_t)src), "r"(bytes) : "memory");
}
__device__ __forceinline__ void bulk_load(uint32_t dst, const void* src, uint32_t bytes, uint32_t bar) {
    asm volatile("cp.async.bulk.shared::cluster.global.mbarrier::complete_tx::bytes [%0], [%1], %2, [%3];"
                 ::"r"(dst), "l"((uint64_t)src), "r"(bytes), "r"(bar) : "memory");
}
__device__ __forceinline__ void bulk_commit() { asm volatile("cp.async.bulk.commit_group;" ::: "memory"); }
__device__ __forceinline__ void bulk_wait_all() { asm volatile("cp.async.bulk.wait_group 0;" ::: "memory"); }
__device__ __forceinline__ void bulk_wait_read() { asm volatile("cp.async.bulk.wait_group.read 0;" ::: "memory"); }

__device__ __forceinline__ void wgmma_fence() { asm volatile("wgmma.fence.sync.aligned;" ::: "memory"); }
__device__ __forceinline__ void wgmma_commit() { asm volatile("wgmma.commit_group.sync.aligned;" ::: "memory"); }
template <int N>
__device__ __forceinline__ void wgmma_wait() { asm volatile("wgmma.wait_group.sync.aligned %0;" ::"n"(N) : "memory"); }

__device__ __forceinline__ uint64_t mkdesc(uint32_t addr, uint32_t lbo, uint32_t sbo, uint32_t swz) {
    return (uint64_t)((addr & 0x3FFFF) >> 4) | ((uint64_t)(lbo >> 4) << 16) | ((uint64_t)(sbo >> 4) << 32) | ((uint64_t)swz << 62);
}
__device__ __forceinline__ uint32_t pack2(float lo, float hi) {
    uint32_t r;
    asm("cvt.rn.bf16x2.f32 %0, %1, %2;" : "=r"(r) : "f"(hi), "f"(lo));
    return r;
}
__device__ __forceinline__ float bf_lo(uint32_t v) { return __uint_as_float(v << 16); }
__device__ __forceinline__ float bf_hi(uint32_t v) { return __uint_as_float(v & 0xFFFF0000u); }
__device__ __forceinline__ void stmatrix4(uint32_t addr, uint32_t r0, uint32_t r1, uint32_t r2, uint32_t r3) {
    asm volatile("stmatrix.sync.aligned.m8n8.x4.shared.b16 [%0], {%1, %2, %3, %4};" ::"r"(addr), "r"(r0), "r"(r1), "r"(r2), "r"(r3) : "memory");
}
__device__ __forceinline__ void stmatrix4t(uint32_t addr, uint32_t r0, uint32_t r1, uint32_t r2, uint32_t r3) {
    asm volatile("stmatrix.sync.aligned.m8n8.x4.trans.shared.b16 [%0], {%1, %2, %3, %4};" ::"r"(addr), "r"(r0), "r"(r1), "r"(r2), "r"(r3) : "memory");
}
__device__ __forceinline__ void ldsm4(uint32_t addr, uint32_t& r0, uint32_t& r1, uint32_t& r2, uint32_t& r3) {
    asm volatile("ldmatrix.sync.aligned.m8n8.x4.shared.b16 {%0, %1, %2, %3}, [%4];" : "=r"(r0), "=r"(r1), "=r"(r2), "=r"(r3) : "r"(addr) : "memory");
}
__device__ __forceinline__ uint4 lds128(uint32_t addr) {
    uint4 v;
    asm volatile("ld.shared.v4.u32 {%0, %1, %2, %3}, [%4];" : "=r"(v.x), "=r"(v.y), "=r"(v.z), "=r"(v.w) : "r"(addr) : "memory");
    return v;
}
__device__ __forceinline__ void sts128(uint32_t addr, uint4 v) {
    asm volatile("st.shared.v4.u32 [%0], {%1, %2, %3, %4};" ::"r"(addr), "r"(v.x), "r"(v.y), "r"(v.z), "r"(v.w) : "memory");
}
__device__ __forceinline__ void sts32(uint32_t addr, uint32_t v) {
    asm volatile("st.shared.u32 [%0], %1;" ::"r"(addr), "r"(v) : "memory");
}
__device__ __forceinline__ float ex2(float x) {
    float r;
    asm("ex2.approx.ftz.f32 %0, %1;" : "=f"(r) : "f"(x));
    return r;
}
__device__ __forceinline__ float rcp_fast(float x) {
    float r;
    asm("rcp.approx.ftz.f32 %0, %1;" : "=f"(r) : "f"(x));
    return r;
}
__device__ __forceinline__ void red_add4(float4* p, float4 v) {
    asm volatile("red.relaxed.gpu.global.add.v4.f32 [%0], {%1, %2, %3, %4};" ::"l"(p), "f"(v.x), "f"(v.y), "f"(v.z), "f"(v.w) : "memory");
}
__device__ __forceinline__ float tanh_fast(float x) {
    float r;
    asm("tanh.approx.f32 %0, %1;" : "=f"(r) : "f"(x));
    return r;
}
__device__ __forceinline__ float gelu_tanh(float u) {
    float z = 0.7978845608028654f * (u + 0.044715f * u * u * u);
    float hu = 0.5f * u;
    return fmaf(hu, tanh_fast(z), hu);
}

template <int N>
__device__ __forceinline__ void zero(float (&a)[N]) {
#pragma unroll
    for (int i = 0; i < N; i++) a[i] = 0.f;
}

template <int N>
__device__ __forceinline__ void pin(float (&a)[N]) {
#pragma unroll
    for (int i = 0; i < N; i++) asm volatile("" : "+f"(a[i])::"memory");
}
__device__ __forceinline__ void pin(uint32_t& a) { asm volatile("" : "+r"(a)::"memory"); }

template <int TA, int TB>
__device__ __forceinline__ void wgmma_n192(float (&d)[96], uint64_t da, uint64_t db, int scale_d) {
    asm volatile("{\n.reg .pred p;\nsetp.ne.b32 p, %98, 0;\n"
        "wgmma.mma_async.sync.aligned.m64n192k16.f32.bf16.bf16 {%0, %1, %2, %3, %4, %5, %6, %7, %8, %9, %10, %11, %12, %13, %14, %15, %16, %17, %18, %19, %20, %21, %22, %23, %24, %25, %26, %27, %28, %29, %30, %31, %32, %33, %34, %35, %36, %37, %38, %39, %40, %41, %42, %43, %44, %45, %46, %47, %48, %49, %50, %51, %52, %53, %54, %55, %56, %57, %58, %59, %60, %61, %62, %63, %64, %65, %66, %67, %68, %69, %70, %71, %72, %73, %74, %75, %76, %77, %78, %79, %80, %81, %82, %83, %84, %85, %86, %87, %88, %89, %90, %91, %92, %93, %94, %95}, %96, %97, p, 1, 1, %99, %100;\n}\n"
        : "+f"(d[0]), "+f"(d[1]), "+f"(d[2]), "+f"(d[3]), "+f"(d[4]), "+f"(d[5]), "+f"(d[6]), "+f"(d[7]), "+f"(d[8]), "+f"(d[9]), "+f"(d[10]), "+f"(d[11]), "+f"(d[12]), "+f"(d[13]), "+f"(d[14]), "+f"(d[15]), "+f"(d[16]), "+f"(d[17]), "+f"(d[18]), "+f"(d[19]), "+f"(d[20]), "+f"(d[21]), "+f"(d[22]), "+f"(d[23]), "+f"(d[24]), "+f"(d[25]), "+f"(d[26]), "+f"(d[27]), "+f"(d[28]), "+f"(d[29]), "+f"(d[30]), "+f"(d[31]), "+f"(d[32]), "+f"(d[33]), "+f"(d[34]), "+f"(d[35]), "+f"(d[36]), "+f"(d[37]), "+f"(d[38]), "+f"(d[39]), "+f"(d[40]), "+f"(d[41]), "+f"(d[42]), "+f"(d[43]), "+f"(d[44]), "+f"(d[45]), "+f"(d[46]), "+f"(d[47]), "+f"(d[48]), "+f"(d[49]), "+f"(d[50]), "+f"(d[51]), "+f"(d[52]), "+f"(d[53]), "+f"(d[54]), "+f"(d[55]), "+f"(d[56]), "+f"(d[57]), "+f"(d[58]), "+f"(d[59]), "+f"(d[60]), "+f"(d[61]), "+f"(d[62]), "+f"(d[63]), "+f"(d[64]), "+f"(d[65]), "+f"(d[66]), "+f"(d[67]), "+f"(d[68]), "+f"(d[69]), "+f"(d[70]), "+f"(d[71]), "+f"(d[72]), "+f"(d[73]), "+f"(d[74]), "+f"(d[75]), "+f"(d[76]), "+f"(d[77]), "+f"(d[78]), "+f"(d[79]), "+f"(d[80]), "+f"(d[81]), "+f"(d[82]), "+f"(d[83]), "+f"(d[84]), "+f"(d[85]), "+f"(d[86]), "+f"(d[87]), "+f"(d[88]), "+f"(d[89]), "+f"(d[90]), "+f"(d[91]), "+f"(d[92]), "+f"(d[93]), "+f"(d[94]), "+f"(d[95])
        : "l"(da), "l"(db), "r"(scale_d), "n"(TA), "n"(TB));
}
template <int TA, int TB>
__device__ __forceinline__ void wgmma_n224(float (&d)[112], uint64_t da, uint64_t db, int scale_d) {
    asm volatile("{\n.reg .pred p;\nsetp.ne.b32 p, %114, 0;\n"
        "wgmma.mma_async.sync.aligned.m64n224k16.f32.bf16.bf16 {%0, %1, %2, %3, %4, %5, %6, %7, %8, %9, %10, %11, %12, %13, %14, %15, %16, %17, %18, %19, %20, %21, %22, %23, %24, %25, %26, %27, %28, %29, %30, %31, %32, %33, %34, %35, %36, %37, %38, %39, %40, %41, %42, %43, %44, %45, %46, %47, %48, %49, %50, %51, %52, %53, %54, %55, %56, %57, %58, %59, %60, %61, %62, %63, %64, %65, %66, %67, %68, %69, %70, %71, %72, %73, %74, %75, %76, %77, %78, %79, %80, %81, %82, %83, %84, %85, %86, %87, %88, %89, %90, %91, %92, %93, %94, %95, %96, %97, %98, %99, %100, %101, %102, %103, %104, %105, %106, %107, %108, %109, %110, %111}, %112, %113, p, 1, 1, %115, %116;\n}\n"
        : "+f"(d[0]), "+f"(d[1]), "+f"(d[2]), "+f"(d[3]), "+f"(d[4]), "+f"(d[5]), "+f"(d[6]), "+f"(d[7]), "+f"(d[8]), "+f"(d[9]), "+f"(d[10]), "+f"(d[11]), "+f"(d[12]), "+f"(d[13]), "+f"(d[14]), "+f"(d[15]), "+f"(d[16]), "+f"(d[17]), "+f"(d[18]), "+f"(d[19]), "+f"(d[20]), "+f"(d[21]), "+f"(d[22]), "+f"(d[23]), "+f"(d[24]), "+f"(d[25]), "+f"(d[26]), "+f"(d[27]), "+f"(d[28]), "+f"(d[29]), "+f"(d[30]), "+f"(d[31]), "+f"(d[32]), "+f"(d[33]), "+f"(d[34]), "+f"(d[35]), "+f"(d[36]), "+f"(d[37]), "+f"(d[38]), "+f"(d[39]), "+f"(d[40]), "+f"(d[41]), "+f"(d[42]), "+f"(d[43]), "+f"(d[44]), "+f"(d[45]), "+f"(d[46]), "+f"(d[47]), "+f"(d[48]), "+f"(d[49]), "+f"(d[50]), "+f"(d[51]), "+f"(d[52]), "+f"(d[53]), "+f"(d[54]), "+f"(d[55]), "+f"(d[56]), "+f"(d[57]), "+f"(d[58]), "+f"(d[59]), "+f"(d[60]), "+f"(d[61]), "+f"(d[62]), "+f"(d[63]), "+f"(d[64]), "+f"(d[65]), "+f"(d[66]), "+f"(d[67]), "+f"(d[68]), "+f"(d[69]), "+f"(d[70]), "+f"(d[71]), "+f"(d[72]), "+f"(d[73]), "+f"(d[74]), "+f"(d[75]), "+f"(d[76]), "+f"(d[77]), "+f"(d[78]), "+f"(d[79]), "+f"(d[80]), "+f"(d[81]), "+f"(d[82]), "+f"(d[83]), "+f"(d[84]), "+f"(d[85]), "+f"(d[86]), "+f"(d[87]), "+f"(d[88]), "+f"(d[89]), "+f"(d[90]), "+f"(d[91]), "+f"(d[92]), "+f"(d[93]), "+f"(d[94]), "+f"(d[95]), "+f"(d[96]), "+f"(d[97]), "+f"(d[98]), "+f"(d[99]), "+f"(d[100]), "+f"(d[101]), "+f"(d[102]), "+f"(d[103]), "+f"(d[104]), "+f"(d[105]), "+f"(d[106]), "+f"(d[107]), "+f"(d[108]), "+f"(d[109]), "+f"(d[110]), "+f"(d[111])
        : "l"(da), "l"(db), "r"(scale_d), "n"(TA), "n"(TB));
}
template <int TA, int TB>
__device__ __forceinline__ void wgmma_n256(float (&d)[128], uint64_t da, uint64_t db, int scale_d) {
    asm volatile("{\n.reg .pred p;\nsetp.ne.b32 p, %130, 0;\n"
        "wgmma.mma_async.sync.aligned.m64n256k16.f32.bf16.bf16 {%0, %1, %2, %3, %4, %5, %6, %7, %8, %9, %10, %11, %12, %13, %14, %15, %16, %17, %18, %19, %20, %21, %22, %23, %24, %25, %26, %27, %28, %29, %30, %31, %32, %33, %34, %35, %36, %37, %38, %39, %40, %41, %42, %43, %44, %45, %46, %47, %48, %49, %50, %51, %52, %53, %54, %55, %56, %57, %58, %59, %60, %61, %62, %63, %64, %65, %66, %67, %68, %69, %70, %71, %72, %73, %74, %75, %76, %77, %78, %79, %80, %81, %82, %83, %84, %85, %86, %87, %88, %89, %90, %91, %92, %93, %94, %95, %96, %97, %98, %99, %100, %101, %102, %103, %104, %105, %106, %107, %108, %109, %110, %111, %112, %113, %114, %115, %116, %117, %118, %119, %120, %121, %122, %123, %124, %125, %126, %127}, %128, %129, p, 1, 1, %131, %132;\n}\n"
        : "+f"(d[0]), "+f"(d[1]), "+f"(d[2]), "+f"(d[3]), "+f"(d[4]), "+f"(d[5]), "+f"(d[6]), "+f"(d[7]), "+f"(d[8]), "+f"(d[9]), "+f"(d[10]), "+f"(d[11]), "+f"(d[12]), "+f"(d[13]), "+f"(d[14]), "+f"(d[15]), "+f"(d[16]), "+f"(d[17]), "+f"(d[18]), "+f"(d[19]), "+f"(d[20]), "+f"(d[21]), "+f"(d[22]), "+f"(d[23]), "+f"(d[24]), "+f"(d[25]), "+f"(d[26]), "+f"(d[27]), "+f"(d[28]), "+f"(d[29]), "+f"(d[30]), "+f"(d[31]), "+f"(d[32]), "+f"(d[33]), "+f"(d[34]), "+f"(d[35]), "+f"(d[36]), "+f"(d[37]), "+f"(d[38]), "+f"(d[39]), "+f"(d[40]), "+f"(d[41]), "+f"(d[42]), "+f"(d[43]), "+f"(d[44]), "+f"(d[45]), "+f"(d[46]), "+f"(d[47]), "+f"(d[48]), "+f"(d[49]), "+f"(d[50]), "+f"(d[51]), "+f"(d[52]), "+f"(d[53]), "+f"(d[54]), "+f"(d[55]), "+f"(d[56]), "+f"(d[57]), "+f"(d[58]), "+f"(d[59]), "+f"(d[60]), "+f"(d[61]), "+f"(d[62]), "+f"(d[63]), "+f"(d[64]), "+f"(d[65]), "+f"(d[66]), "+f"(d[67]), "+f"(d[68]), "+f"(d[69]), "+f"(d[70]), "+f"(d[71]), "+f"(d[72]), "+f"(d[73]), "+f"(d[74]), "+f"(d[75]), "+f"(d[76]), "+f"(d[77]), "+f"(d[78]), "+f"(d[79]), "+f"(d[80]), "+f"(d[81]), "+f"(d[82]), "+f"(d[83]), "+f"(d[84]), "+f"(d[85]), "+f"(d[86]), "+f"(d[87]), "+f"(d[88]), "+f"(d[89]), "+f"(d[90]), "+f"(d[91]), "+f"(d[92]), "+f"(d[93]), "+f"(d[94]), "+f"(d[95]), "+f"(d[96]), "+f"(d[97]), "+f"(d[98]), "+f"(d[99]), "+f"(d[100]), "+f"(d[101]), "+f"(d[102]), "+f"(d[103]), "+f"(d[104]), "+f"(d[105]), "+f"(d[106]), "+f"(d[107]), "+f"(d[108]), "+f"(d[109]), "+f"(d[110]), "+f"(d[111]), "+f"(d[112]), "+f"(d[113]), "+f"(d[114]), "+f"(d[115]), "+f"(d[116]), "+f"(d[117]), "+f"(d[118]), "+f"(d[119]), "+f"(d[120]), "+f"(d[121]), "+f"(d[122]), "+f"(d[123]), "+f"(d[124]), "+f"(d[125]), "+f"(d[126]), "+f"(d[127])
        : "l"(da), "l"(db), "r"(scale_d), "n"(TA), "n"(TB));
}
template <int TA, int TB>
__device__ __forceinline__ void wgmma_n64(float (&d)[32], uint64_t da, uint64_t db, int scale_d) {
    asm volatile("{\n.reg .pred p;\nsetp.ne.b32 p, %34, 0;\n"
        "wgmma.mma_async.sync.aligned.m64n64k16.f32.bf16.bf16 {%0, %1, %2, %3, %4, %5, %6, %7, %8, %9, %10, %11, %12, %13, %14, %15, %16, %17, %18, %19, %20, %21, %22, %23, %24, %25, %26, %27, %28, %29, %30, %31}, %32, %33, p, 1, 1, %35, %36;\n}\n"
        : "+f"(d[0]), "+f"(d[1]), "+f"(d[2]), "+f"(d[3]), "+f"(d[4]), "+f"(d[5]), "+f"(d[6]), "+f"(d[7]), "+f"(d[8]), "+f"(d[9]), "+f"(d[10]), "+f"(d[11]), "+f"(d[12]), "+f"(d[13]), "+f"(d[14]), "+f"(d[15]), "+f"(d[16]), "+f"(d[17]), "+f"(d[18]), "+f"(d[19]), "+f"(d[20]), "+f"(d[21]), "+f"(d[22]), "+f"(d[23]), "+f"(d[24]), "+f"(d[25]), "+f"(d[26]), "+f"(d[27]), "+f"(d[28]), "+f"(d[29]), "+f"(d[30]), "+f"(d[31])
        : "l"(da), "l"(db), "r"(scale_d), "n"(TA), "n"(TB));
}
template <int TB>
__device__ __forceinline__ void wgmma_rs_n32(float (&d)[16], uint32_t a0, uint32_t a1, uint32_t a2, uint32_t a3, uint64_t db, int scale_d) {
    asm volatile("{\n.reg .pred p;\nsetp.ne.b32 p, %21, 0;\n"
        "wgmma.mma_async.sync.aligned.m64n32k16.f32.bf16.bf16 {%0, %1, %2, %3, %4, %5, %6, %7, %8, %9, %10, %11, %12, %13, %14, %15}, {%16, %17, %18, %19}, %20, p, 1, 1, %22;\n}\n"
        : "+f"(d[0]), "+f"(d[1]), "+f"(d[2]), "+f"(d[3]), "+f"(d[4]), "+f"(d[5]), "+f"(d[6]), "+f"(d[7]), "+f"(d[8]), "+f"(d[9]), "+f"(d[10]), "+f"(d[11]), "+f"(d[12]), "+f"(d[13]), "+f"(d[14]), "+f"(d[15])
        : "r"(a0), "r"(a1), "r"(a2), "r"(a3), "l"(db), "r"(scale_d), "n"(TB));
}
template <int TB>
__device__ __forceinline__ void wgmma_rs_n40(float (&d)[20], uint32_t a0, uint32_t a1, uint32_t a2, uint32_t a3, uint64_t db, int scale_d) {
    asm volatile("{\n.reg .pred p;\nsetp.ne.b32 p, %25, 0;\n"
        "wgmma.mma_async.sync.aligned.m64n40k16.f32.bf16.bf16 {%0, %1, %2, %3, %4, %5, %6, %7, %8, %9, %10, %11, %12, %13, %14, %15, %16, %17, %18, %19}, {%20, %21, %22, %23}, %24, p, 1, 1, %26;\n}\n"
        : "+f"(d[0]), "+f"(d[1]), "+f"(d[2]), "+f"(d[3]), "+f"(d[4]), "+f"(d[5]), "+f"(d[6]), "+f"(d[7]), "+f"(d[8]), "+f"(d[9]), "+f"(d[10]), "+f"(d[11]), "+f"(d[12]), "+f"(d[13]), "+f"(d[14]), "+f"(d[15]), "+f"(d[16]), "+f"(d[17]), "+f"(d[18]), "+f"(d[19])
        : "r"(a0), "r"(a1), "r"(a2), "r"(a3), "l"(db), "r"(scale_d), "n"(TB));
}

struct Ring {
    uint32_t s, ph;
    __device__ __forceinline__ void next() {
        if (++s == NSTAGE) { s = 0; ph ^= 1; }
    }
};

template <int MODE, int NACC>
__device__ __forceinline__ void mainloop(float (&acc)[NACC], int nkb, Ring& ring, uint32_t sbase, uint32_t bar_full,
                                         uint32_t bar_empty, int wg, int lane) {
    uint32_t prev_s = 0;
#pragma unroll 1
    for (int kb = 0; kb < nkb; kb++) {
        const uint32_t slot = sbase + ring.s * SLOT;
        TR(threadIdx.x == 128 && kb < 64, MODE * 64 + kb);
        mbar_wait<0>(bar_full + 8 * ring.s, ring.ph);
        wgmma_fence();
#pragma unroll
        for (int j = 0; j < BK / 16; j++) {
            if constexpr (MODE == 0) {
                wgmma_n192<0, 1>(acc, mkdesc(slot + wg * (BK * 128) + j * 32, 16, BK * 16, BK == 64 ? 1 : 2), mkdesc(slot + BOFF + j * 2048, BK * 128, 1024, 1), 1);
            } else if constexpr (MODE == 1) {
                wgmma_n224<1, 1>(acc, mkdesc(slot + wg * (BK * 128) + j * 2048, BK * 128, 1024, 1), mkdesc(slot + BOFF + j * 1024, BK * 64, 512, 2), 1);
            } else {
                wgmma_n256<1, 1>(acc, mkdesc(slot + wg * (BK * 128) + j * 2048, BK * 128, 1024, 1), mkdesc(slot + BOFF + j * 2048, BK * 128, 1024, 1), 1);
            }
        }
        wgmma_commit();
        if (kb > 0) {
            wgmma_wait<1>();
            if (lane == 0) mbar_arrive(bar_empty + 8 * prev_s);
        }
        prev_s = ring.s;
        ring.next();
    }
    wgmma_wait<0>();
    if (lane == 0) mbar_arrive(bar_empty + 8 * prev_s);
}

template <int NC>
__device__ __forceinline__ void dual_softmax(const uint32_t (&pk)[NC][4], uint32_t (&P)[NC][4], uint32_t (&M)[NC][4]) {
    constexpr float L2E = 1.4426950408889634f;
    uint32_t mm[NC];
#pragma unroll
    for (int c = 0; c < NC; c++) {
        __nv_bfloat162 a0 = *(const __nv_bfloat162*)&pk[c][0], a1 = *(const __nv_bfloat162*)&pk[c][1];
        __nv_bfloat162 a2 = *(const __nv_bfloat162*)&pk[c][2], a3 = *(const __nv_bfloat162*)&pk[c][3];
        __nv_bfloat162 mx = __hmax2(__hmax2(a0, a1), __hmax2(a2, a3));
        __nv_bfloat162 mn = __hmin2(__hmin2(a0, a1), __hmin2(a2, a3));
        const uint32_t umx = *(const uint32_t*)&mx, umn = (*(const uint32_t*)&mn) ^ 0x80008000u;
        const uint32_t lo = __byte_perm(umx, umn, 0x5410), hi = __byte_perm(umx, umn, 0x7632);
        __nv_bfloat162 r = __hmax2(*(const __nv_bfloat162*)&lo, *(const __nv_bfloat162*)&hi);
        mm[c] = *(const uint32_t*)&r;
    }
#pragma unroll
    for (int o = 1; o <= 2; o <<= 1) {
        uint32_t t[NC];
#pragma unroll
        for (int c = 0; c < NC; c++) t[c] = __shfl_xor_sync(0xffffffffu, mm[c], o);
#pragma unroll
        for (int c = 0; c < NC; c++) {
            __nv_bfloat162 r = __hmax2(*(const __nv_bfloat162*)&mm[c], *(const __nv_bfloat162*)&t[c]);
            mm[c] = *(const uint32_t*)&r;
        }
    }
    float ep[NC][8], em[NC][8], sp[NC], sm[NC];
#pragma unroll
    for (int c = 0; c < NC; c++) {
        const float mxs = bf_lo(mm[c]) * L2E, mns = bf_hi(mm[c]) * L2E;
#pragma unroll
        for (int i = 0; i < 4; i++) {
            const float a = bf_lo(pk[c][i]), b = bf_hi(pk[c][i]);
            ep[c][2 * i] = ex2(fmaf(a, L2E, -mxs));
            ep[c][2 * i + 1] = ex2(fmaf(b, L2E, -mxs));
            em[c][2 * i] = ex2(fmaf(a, -L2E, -mns));
            em[c][2 * i + 1] = ex2(fmaf(b, -L2E, -mns));
        }
        sp[c] = ((ep[c][0] + ep[c][1]) + (ep[c][2] + ep[c][3])) + ((ep[c][4] + ep[c][5]) + (ep[c][6] + ep[c][7]));
        sm[c] = ((em[c][0] + em[c][1]) + (em[c][2] + em[c][3])) + ((em[c][4] + em[c][5]) + (em[c][6] + em[c][7]));
    }
#pragma unroll
    for (int o = 1; o <= 2; o <<= 1) {
        float tp[NC], tm[NC];
#pragma unroll
        for (int c = 0; c < NC; c++) {
            tp[c] = __shfl_xor_sync(0xffffffffu, sp[c], o);
            tm[c] = __shfl_xor_sync(0xffffffffu, sm[c], o);
        }
#pragma unroll
        for (int c = 0; c < NC; c++) { sp[c] += tp[c]; sm[c] += tm[c]; }
    }
#pragma unroll
    for (int c = 0; c < NC; c++) {
        const float rp = rcp_fast(sp[c]), rm = rcp_fast(sm[c]);
#pragma unroll
        for (int i = 0; i < 4; i++) {
            P[c][i] = pack2(ep[c][2 * i] * rp, ep[c][2 * i + 1] * rp);
            M[c][i] = pack2(em[c][2 * i] * rm, em[c][2 * i + 1] * rm);
        }
    }
}

template <int NR>
__device__ __forceinline__ void ln_rows(const __nv_bfloat16* x, const __nv_bfloat16* gate_w, int row0, int row_end, int lane) {
    uint4 v[NR][4], gw[4];
    float sh[NR], red[NR][3];
#pragma unroll
    for (int h = 0; h < NR; h++) {
        const int row = min(row0 + h, row_end - 1);
#pragma unroll
        for (int c = 0; c < 4; c++) v[h][c] = __ldg((const uint4*)(x + (size_t)row * D_) + c * 32 + lane);
        sh[h] = __bfloat162float(__ldg(x + (size_t)row * D_));
    }
#pragma unroll
    for (int c = 0; c < 4; c++) gw[c] = __ldg((const uint4*)gate_w + c * 32 + lane);
#pragma unroll
    for (int h = 0; h < NR; h++) {
        float s0 = 0.f, s1 = 0.f, q0 = 0.f, q1 = 0.f, d0 = 0.f, d1 = 0.f;
#pragma unroll
        for (int c = 0; c < 4; c++) {
            const uint32_t w[4] = {v[h][c].x, v[h][c].y, v[h][c].z, v[h][c].w};
            const uint32_t q[4] = {gw[c].x, gw[c].y, gw[c].z, gw[c].w};
#pragma unroll
            for (int k = 0; k < 4; k++) {
                const float a = bf_lo(w[k]) - sh[h], b = bf_hi(w[k]) - sh[h];
                s0 += a; s1 += b;
                q0 = fmaf(a, a, q0); q1 = fmaf(b, b, q1);
                d0 = fmaf(bf_lo(w[k]), bf_lo(q[k]), d0);
                d1 = fmaf(bf_hi(w[k]), bf_hi(q[k]), d1);
            }
        }
        red[h][0] = s0 + s1; red[h][1] = q0 + q1; red[h][2] = d0 + d1;
    }
#pragma unroll
    for (int o = 16; o > 0; o >>= 1) {
        float t[NR][3];
#pragma unroll
        for (int h = 0; h < NR; h++)
#pragma unroll
            for (int k = 0; k < 3; k++) t[h][k] = __shfl_xor_sync(0xffffffffu, red[h][k], o);
#pragma unroll
        for (int h = 0; h < NR; h++)
#pragma unroll
            for (int k = 0; k < 3; k++) red[h][k] += t[h][k];
    }
#pragma unroll
    for (int h = 0; h < NR; h++) {
        if (row0 + h < row_end) {
            const float ms = red[h][0] * (1.f / D_);
            const float var = fmaxf(red[h][1] * (1.f / D_) - ms * ms, 0.f);
            const float rstd = rsqrtf(var + 1e-5f);
            const float nm = -(ms + sh[h]) * rstd;
            uint4* hr = (uint4*)(g_h + (size_t)(row0 + h) * D_) + lane;
#pragma unroll
            for (int c = 0; c < 4; c++) {
                uint4 o;
                o.x = pack2(fmaf(bf_lo(v[h][c].x), rstd, nm), fmaf(bf_hi(v[h][c].x), rstd, nm));
                o.y = pack2(fmaf(bf_lo(v[h][c].y), rstd, nm), fmaf(bf_hi(v[h][c].y), rstd, nm));
                o.z = pack2(fmaf(bf_lo(v[h][c].z), rstd, nm), fmaf(bf_hi(v[h][c].z), rstd, nm));
                o.w = pack2(fmaf(bf_lo(v[h][c].w), rstd, nm), fmaf(bf_hi(v[h][c].w), rstd, nm));
                hr[c * 32] = o;
            }
            if (lane == 0) g_gate[row0 + h] = 1.f / (1.f + __expf(-red[h][2]));
        }
    }
}

__device__ __forceinline__ void role_done() {
    unsigned old = atomicAdd(&g_flags[FL_EXIT * 32], 1u);
    if (old == 3 * NCTA - 1) {
        for (int i = 0; i < FL_COUNT; i++) g_flags[i * 32] = 0;
    }
}

struct Params {
    const __nv_bfloat16* x;
    const __nv_bfloat16* wphi;
    const __nv_bfloat16* b1;
    const __nv_bfloat16* b2;
    const __nv_bfloat16* gate_w;
};

__global__ void __launch_bounds__(NTHREADS, 1)
fused_kernel(const __grid_constant__ CUtensorMap m_x, const __grid_constant__ CUtensorMap m_wqkv,
             const __grid_constant__ CUtensorMap m_h, const __grid_constant__ CUtensorMap m_w1,
             const __grid_constant__ CUtensorMap m_w2, const __grid_constant__ CUtensorMap m_u,
             const __grid_constant__ CUtensorMap m_o, const __grid_constant__ CUtensorMap m_wo,
             const __grid_constant__ CUtensorMap m_os, const __grid_constant__ CUtensorMap m_out, const Params prm) {
    extern __shared__ uint8_t smem_raw[];
    const uint32_t sbase = (smem_u32(smem_raw) + 1023u) & ~1023u;
    const uint32_t bar_full = sbase + OFF_BAR;
    const uint32_t bar_empty = bar_full + 8 * NSTAGE;
    const uint32_t bar_stg_full = bar_empty + 8 * NSTAGE;
    const uint32_t bar_stg_empty = bar_stg_full + 8;
    const uint32_t bar_part = bar_stg_empty + 8;
    const uint32_t bar_w = bar_part + 8;
    const uint32_t bar_ln = bar_w + 8;
    const uint32_t bar_phi = bar_ln + 8;
    const uint32_t bar_kvd = bar_phi + 8;
    const uint32_t bar_kvx = bar_kvd + 8;
    const uint32_t bar_od = bar_kvx + 8;
    const uint32_t stg = sbase + OFF_STG;

    const int tid = threadIdx.x;
    const int warp = tid >> 5, lane = tid & 31;
    const int cta = blockIdx.x;
    const int r = cta & 1, p = cta >> 1;
    const int hp = p & 15, tg = p >> 4;
    const int tok_a = tg * 4 + r, tok_b = tg * 4 + 2 + r;
    const int ft = p & 15, dt = (p >> 4) * 2 + r;
    const int st = (p & 7) * 2 + r, nt = (p >> 3) & 3, kh = p >> 5;
    const int nB = kh ? FB - N0 : N0;
    const int l7 = lane & 7, lb3 = (lane >> 3) & 1, lb4 = lane >> 4;

    if (tid == 0) {
        for (int i = 0; i < NSTAGE; i++) {
            mbar_init(bar_full + 8 * i, 1);
            mbar_init(bar_empty + 8 * i, 8);
        }
        mbar_init(bar_stg_full, 8);
        mbar_init(bar_stg_empty, 1);
        mbar_init(bar_part, 1);
        mbar_init(bar_w, 1);
        mbar_init(bar_ln, 8);
        mbar_init(bar_phi, 1);
        mbar_init(bar_kvd, 8);
        mbar_init(bar_kvx, 1);
        mbar_init(bar_od, 8);
        fence_async_smem();
    }
    __syncthreads();
    TL(tid == 128, 0);
    TLG(tid == 128, 31);

    if (warp >= 8) {
      asm volatile("setmaxnreg.dec.sync.aligned.u32 120;");
      if (warp == 8) {
        if (lane == 0) {
            uint32_t fb = bar_full, dst = sbase, par = 1;
            auto phase = [&](const CUtensorMap* ma, int a1, int a2, bool a_on_0, const CUtensorMap* mb, int b0, int b2, int k0, uint32_t bytes, int cnt) {
#pragma unroll 1
                for (int i = 0; i < cnt; i++) {
                    mbar_wait<2>(fb + 8 * NSTAGE, par);
                    mbar_expect_tx(fb, bytes);
                    tma3d(dst, ma, a_on_0 ? k0 : 0, a_on_0 ? a1 : k0, a2, fb);
                    tma3d(dst + BOFF, mb, b0, k0, b2, fb);
                    k0 += BK;
                    fb += 8; dst += SLOT;
                    if (fb == bar_full + 8 * NSTAGE) { fb = bar_full; dst = sbase; par ^= 1; }
                }
            };
            auto dep = [&](int flag, unsigned target, int tl) {
                TL(true, tl);
                wait_flag<2>(&g_flags[flag * 32], target);
                fence_async_glob();
                TL(true, tl + 1);
            };
            phase(&m_x, tok_a * 128, 0, true, &m_wqkv, hp * 64, 0, 0, BK * 640, 1024 / BK);
            dep(FL_LN, NCTA, 20);
            phase(&m_h, 0, dt * 2, false, &m_w1, 0, ft * 7, 0, BK * 704, 2048 / BK);
            phase(&m_x, tok_b * 128, 0, true, &m_wqkv, hp * 64, 0, 0, BK * 640, 1024 / BK);
            dep(FL_U + nt, 32, 22);
            phase(&m_w2, 0, st * 2, false, &m_u, 0, nt * 4, kh ? N0 * BK : 0, BK * 768, nB);
            dep(FL_O + st, 16, 24);
            phase(&m_o, 0, st * 2, false, &m_wo, 0, nt * 4, kh ? 512 : 0, BK * 768, 512 / BK);
            role_done();
        }
      } else {
        const int et = tid - 288, sw = warp - 9;
        const int g8 = lane >> 2, t4 = lane & 3;
        {
            for (int idx = et; idx < 256; idx += 96) {
                const int k = (idx >> 2) & 31, u = idx & 3, h = idx >> 7;
                sts128(sbase + OFF_WPHI + h * 4096 + k * 128 + ((u ^ (k & 7)) << 4),
                       __ldg((const uint4*)(prm.wphi + ((size_t)(hp * 2 + h) * 32 + k) * 32 + u * 8)));
            }
#pragma unroll 1
            for (int pr = sw; pr < 4; pr += 3) ln_rows<2>(prm.x, prm.gate_w, cta * 16 + 8 + pr * 2, cta * 16 + 16, lane);
            TL(et == 0, 18);
            if (tg == 0 && r == 0) {
#pragma unroll
                for (int i = 0; i < 16; i++) g_kvsum[(hp * 16 + i) * 96 + et] = make_float4(0.f, 0.f, 0.f, 0.f);
            }
            fence_async_glob();
            fence_async_smem();
            bar_sync(1, 96);
            if (et == 0) {
                mbar_arrive(bar_w);
                mbar_wait<1>(bar_ln, 0);
                flag_add(&g_flags[FL_LN * 32]);
            }
            TL(et == 0, 11);
        }

#pragma unroll 1
        for (int tile = 0; tile < 2; tile++) {
            if (tile) {
                mbar_wait<1>(bar_stg_full, 1);
#pragma unroll 1
                for (int idx = et; idx < 896; idx += 96) {
                    uint4 a[4];
                    float b[4];
                    const int u = idx & 15;
#pragma unroll
                    for (int h = 0; h < 4; h++) {
                        const int row = (idx >> 4) + h * 56;
                        a[h] = lds128(stg + row * 256 + ((u ^ (row & 7)) << 4));
                        b[h] = __bfloat162float(__ldg(prm.b1 + ft * 224 + row));
                    }
#pragma unroll
                    for (int h = 0; h < 4; h++) {
                        const int row = (idx >> 4) + h * 56;
                        const uint32_t av[4] = {a[h].x, a[h].y, a[h].z, a[h].w};
                        uint32_t ov[4];
#pragma unroll
                        for (int k = 0; k < 4; k++) {
                            uint32_t tsum = pack2(bf_lo(av[k]) + b[h], bf_hi(av[k]) + b[h]);
                            ov[k] = pack2(gelu_tanh(bf_lo(tsum)), gelu_tanh(bf_hi(tsum)));
                        }
                        *(uint4*)(g_u + (size_t)(ft * 224 + row) * D_ + dt * 128 + u * 8) = make_uint4(ov[0], ov[1], ov[2], ov[3]);
                    }
                }
                fence_async_glob();
                bar_sync(1, 96);
                if (et == 0) {
                    mbar_arrive(bar_stg_empty);
                    flag_add(&g_flags[(FL_U + (dt >> 1)) * 32]);
                }
                TL(et == 0, 13);
            }
            mbar_wait<1>(bar_stg_full, 0);
            for (int idx = et; idx < 256; idx += 96)
                sts128(stg + 32768 + idx * 128 + ((4 ^ (idx & 7)) << 4), make_uint4(0x3F803F80u, 0x3F803F80u, 0x3F803F80u, 0x3F803F80u));
#pragma unroll 1
            for (int it = sw * 2; it < 16; it += (it & 1) ? 5 : 1) {
                const int rb = it >> 1, which = it & 1;
                const uint32_t rowa = stg + (rb * 16 + l7 + lb3 * 8) * 128;
                uint32_t pk[4][4], P[4][4], M[4][4];
#pragma unroll
                for (int j = 0; j < 4; j++)
                    ldsm4(rowa + which * 16384 + (((j * 2 + lb4) ^ l7) << 4), pk[(j >> 1) * 2][(j & 1) * 2], pk[(j >> 1) * 2 + 1][(j & 1) * 2],
                          pk[(j >> 1) * 2][(j & 1) * 2 + 1], pk[(j >> 1) * 2 + 1][(j & 1) * 2 + 1]);
                dual_softmax<4>(pk, P, M);
                if (which == 0) {
                    uint4* dst = &g_pq[(size_t)((cta * 16 + tile * 8 + rb) * 8) * 32 + lane];
#pragma unroll
                    for (int hh = 0; hh < 2; hh++) {
                        dst[(hh * 4 + 0) * 32] = make_uint4(P[2 * hh][0], P[2 * hh + 1][0], P[2 * hh][1], P[2 * hh + 1][1]);
                        dst[(hh * 4 + 1) * 32] = make_uint4(P[2 * hh][2], P[2 * hh + 1][2], P[2 * hh][3], P[2 * hh + 1][3]);
                        dst[(hh * 4 + 2) * 32] = make_uint4(M[2 * hh][0], M[2 * hh + 1][0], M[2 * hh][1], M[2 * hh + 1][1]);
                        dst[(hh * 4 + 3) * 32] = make_uint4(M[2 * hh][2], M[2 * hh + 1][2], M[2 * hh][3], M[2 * hh + 1][3]);
                    }
                } else {
#pragma unroll
                    for (int hh = 0; hh < 2; hh++) {
                        const uint32_t base = rowa + hh * 16384;
                        stmatrix4(base + (((0 + lb4) ^ l7) << 4), P[2 * hh][0], P[2 * hh + 1][0], P[2 * hh][1], P[2 * hh + 1][1]);
                        stmatrix4(base + (((2 + lb4) ^ l7) << 4), P[2 * hh][2], P[2 * hh + 1][2], P[2 * hh][3], P[2 * hh + 1][3]);
                        stmatrix4(base + (((4 + lb4) ^ l7) << 4), M[2 * hh][0], M[2 * hh + 1][0], M[2 * hh][1], M[2 * hh + 1][1]);
                        stmatrix4(base + (((6 + lb4) ^ l7) << 4), M[2 * hh][2], M[2 * hh + 1][2], M[2 * hh][3], M[2 * hh + 1][3]);
                    }
                }
            }
            fence_async_smem();
            if (tile == 0 && et == 0) wait_flag<1>(&g_flags[FL_LN * 32], NCTA);
            bar_sync(1, 96);
            if (et == 0) mbar_arrive(bar_phi);
            TL(et == 0, tile ? 14 : 12);
        }
        if (et == 0) {
            mbar_wait<1>(bar_kvd, 1);
            flag_add(&g_flags[(FL_KV + hp) * 32]);
            wait_flag<1>(&g_flags[(FL_KV + hp) * 32], 8);
        }
        bar_sync(1, 96);
        TL(et == 0, 15);
#pragma unroll
        for (int hh = 0; hh < 2; hh++) {
            float4 sv[8];
#pragma unroll
            for (int i = 0; i < 8; i++) sv[i] = __ldcg(&g_kvsum[((hp * 2 + hh) * 8 + i) * 96 + et]);
            const uint32_t base = stg + 32768 + hh * 8192 + (sw * 16 + g8) * 128 + t4 * 4;
#pragma unroll
            for (int i = 0; i < 8; i++) {
                sts32(base + ((i ^ g8) << 4), pack2(sv[i].x, sv[i].y));
                if (sw < 2) sts32(base + 1024 + ((i ^ g8) << 4), pack2(sv[i].z, sv[i].w));
            }
        }
        fence_async_smem();
        bar_sync(1, 96);
        TL(et == 0, 29);
        if (et == 0) {
            mbar_arrive(bar_kvx);
            mbar_wait<1>(bar_od, 0);
            tma3d_store(&m_os, stg, 0, hp * 64, tok_a * 2);
            tma3d_store(&m_os, stg + 16384, 0, hp * 64, tok_b * 2);
            bulk_commit();
            bulk_wait_all();
            fence_async_glob();
            flag_add(&g_flags[(FL_O + tok_a) * 32]);
            asm volatile("red.relaxed.gpu.global.add.u32 [%0], 1;" ::"l"(&g_flags[(FL_O + tok_b) * 32]) : "memory");
            TL(true, 16);
            if (kh) {
                wait_flag<1>(&g_flags[(FL_PART + st * 4 + nt) * 32], 1);
                fence_async_glob();
                mbar_expect_tx(bar_part, 65536);
                const uint8_t* src = (const uint8_t*)&g_part[(size_t)(st * 4 + nt) * 16 * 256];
                for (int i = 0; i < 4; i++) bulk_load(stg + i * 16384, src + i * 16384, 16384, bar_part);
            }
        }
        if (tid == 288) role_done();
      }
    } else {
        asm volatile("setmaxnreg.inc.sync.aligned.u32 192;");
        const int wg = warp >> 2, wq = warp & 3;
        const int mrow = wg * 64 + wq * 16 + lb3 * 8 + l7;
        Ring ring{0, 0};
        ln_rows<1>(prm.x, prm.gate_w, cta * 16 + warp, cta * 16 + 8, lane);
        fence_async_glob();
        __syncwarp();
        if (lane == 0) mbar_arrive(bar_ln);

        auto kv_section = [&](uint32_t parity) {
            mbar_wait<0>(bar_phi, parity);
            float c[32];
            zero(c);
            pin(c);
            wgmma_fence();
#pragma unroll
            for (int ks = 0; ks < 8; ks++)
                wgmma_n64<1, 1>(c, mkdesc(stg + 32768 + wg * 16384 + ks * 2048, 8192, 1024, 1), mkdesc(stg + wg * 16384 + ks * 2048, 8192, 1024, 1), 1);
            wgmma_commit();
            wgmma_wait<0>();
            pin(c);
            if (wq < 3) {
#pragma unroll
                for (int i = 0; i < 8; i++)
                    red_add4(&g_kvsum[((hp * 2 + wg) * 8 + i) * 96 + wq * 32 + lane],
                             make_float4(c[4 * i], c[4 * i + 1], wq == 2 ? 0.f : c[4 * i + 2], wq == 2 ? 0.f : c[4 * i + 3]));
            }
            __syncwarp();
            if (lane == 0) mbar_arrive(bar_kvd);
        };

#pragma unroll 1
        for (int pass = 0; pass < 2; pass++) {
            {
                float acc[96];
                zero(acc);
                mainloop<0>(acc, 1024 / BK, ring, sbase, bar_full, bar_empty, wg, lane);
                TL(tid == 128, pass ? 5 : 1);
                mbar_wait<0>(pass ? bar_stg_empty : bar_w, 0);
                float pf[4][16];
                {
                    uint32_t a[8][4];
#pragma unroll
                    for (int j = 0; j < 8; j++) {
                        a[j][0] = pack2(acc[8 * j], acc[8 * j + 1]); a[j][1] = pack2(acc[8 * j + 2], acc[8 * j + 3]);
                        a[j][2] = pack2(acc[8 * j + 4], acc[8 * j + 5]); a[j][3] = pack2(acc[8 * j + 6], acc[8 * j + 7]);
                    }
                    zero(pf[0]); zero(pf[1]); zero(pf[2]); zero(pf[3]);
                    pin(pf[0]); pin(pf[1]); pin(pf[2]); pin(pf[3]);
#pragma unroll
                    for (int j = 0; j < 8; j++) { pin(a[j][0]); pin(a[j][1]); pin(a[j][2]); pin(a[j][3]); }
                    wgmma_fence();
#pragma unroll
                    for (int j = 0; j < 8; j++)
                        wgmma_rs_n32<1>(pf[j >> 1], a[j][0], a[j][1], a[j][2], a[j][3], mkdesc(sbase + OFF_WPHI + (j & 3) * 2048, 4096, 1024, 1), 1);
                    wgmma_commit();
                }
                const uint32_t base = stg + mrow * 128;
#pragma unroll
                for (int j = 0; j < 4; j++)
                    stmatrix4(base + 32768 + (j >> 1) * 16384 + ((((j & 1) * 2 + lb4) ^ l7) << 4),
                              pack2(acc[64 + 8 * j], acc[65 + 8 * j]), pack2(acc[66 + 8 * j], acc[67 + 8 * j]),
                              pack2(acc[68 + 8 * j], acc[69 + 8 * j]), pack2(acc[70 + 8 * j], acc[71 + 8 * j]));
                wgmma_wait<0>();
#pragma unroll
                for (int j = 0; j < 8; j++) {
                    const float* f = &pf[j >> 1][(j & 1) * 8];
                    stmatrix4(base + (j >> 2) * 16384 + ((((j & 3) * 2 + lb4) ^ l7) << 4),
                              pack2(f[0], f[1]), pack2(f[2], f[3]), pack2(f[4], f[5]), pack2(f[6], f[7]));
                }
                fence_async_smem();
                __syncwarp();
                if (lane == 0) mbar_arrive(bar_stg_full);
                TL(tid == 128, pass ? 6 : 2);
            }
            if (pass == 0) {
                float acc[112];
                zero(acc);
                mainloop<1>(acc, 2048 / BK, ring, sbase, bar_full, bar_empty, wg, lane);
                TL(tid == 128, 3);
                kv_section(0);
                bar_sync(2, 256);
                const uint32_t base = stg + (lb4 * 8 + l7) * 256 + (((wg * 8 + wq * 2 + lb3) ^ l7) << 4);
#pragma unroll
                for (int jb = 0; jb < 14; jb++)
                    stmatrix4t(base + jb * 4096, pack2(acc[8 * jb], acc[8 * jb + 1]), pack2(acc[8 * jb + 2], acc[8 * jb + 3]),
                               pack2(acc[8 * jb + 4], acc[8 * jb + 5]), pack2(acc[8 * jb + 6], acc[8 * jb + 7]));
                __syncwarp();
                if (lane == 0) mbar_arrive(bar_stg_full);
                TL(tid == 128, 4);
            }
        }
        float acc[128];
        zero(acc);
        const int grow = st * 128 + wg * 64 + wq * 16 + (lane >> 2);
        mainloop<2>(acc, S1, ring, sbase, bar_full, bar_empty, wg, lane);
        TL(tid == 128, 26);
        kv_section(1);
        TL(tid == 128, 27);
        mainloop<2>(acc, S2 - S1, ring, sbase, bar_full, bar_empty, wg, lane);
        TL(tid == 128, 28);
        {
            const uint4* src = &g_pq[(size_t)((cta * 16 + wg * 8 + wq) * 8) * 32 + lane];
            const int orow = (wg ? tok_b : tok_a) * 128 + wq * 16 + (lane >> 2);
            uint4 qn[4];
#pragma unroll
            for (int i = 0; i < 4; i++) qn[i] = __ldcg(src + i * 32);
            const float ga0 = __ldcg(&g_gate[orow]), ga1 = __ldcg(&g_gate[orow + 8]);
            const float gb0 = __ldcg(&g_gate[orow + 64]), gb1 = __ldcg(&g_gate[orow + 72]);
            mbar_wait<0>(bar_kvx, 0);
#pragma unroll 1
            for (int un = 0; un < 4; un++) {
                const int mb = un >> 1, hh = un & 1;
                uint4 q[4];
#pragma unroll
                for (int i = 0; i < 4; i++) q[i] = qn[i];
                if (un < 3) {
                    const uint4* nsrc = src + (((un + 1) >> 1) * 32 + ((un + 1) & 1) * 4) * 32;
#pragma unroll
                    for (int i = 0; i < 4; i++) qn[i] = __ldcg(nsrc + i * 32);
                }
                const float gt0 = mb ? gb0 : ga0, gt1 = mb ? gb1 : ga1;
                float o[20];
                zero(o);
                pin(o);
#pragma unroll
                for (int i = 0; i < 4; i++) { pin(q[i].x); pin(q[i].y); pin(q[i].z); pin(q[i].w); }
                wgmma_fence();
#pragma unroll
                for (int j = 0; j < 4; j++)
                    wgmma_rs_n40<0>(o, q[j].x, q[j].y, q[j].z, q[j].w, mkdesc(stg + 32768 + hh * 8192 + j * 32, 16, 1024, 1), 1);
                wgmma_commit();
                wgmma_wait<0>();
                pin(o);
#pragma unroll
                for (int i = 0; i < 4; i++) { pin(q[i].x); pin(q[i].y); pin(q[i].z); pin(q[i].w); }
                const float s0 = gt0 * rcp_fast(o[16] + 1e-6f), s1 = gt1 * rcp_fast(o[18] + 1e-6f);
                const uint32_t base = stg + wg * 16384 + mb * 8192 + (hh * 32 + lb4 * 8 + l7) * 128 + (((wq * 2 + lb3) ^ l7) << 4);
                stmatrix4t(base, pack2(o[0] * s0, o[1] * s0), pack2(o[2] * s1, o[3] * s1),
                           pack2(o[4] * s0, o[5] * s0), pack2(o[6] * s1, o[7] * s1));
                stmatrix4t(base + 2048, pack2(o[8] * s0, o[9] * s0), pack2(o[10] * s1, o[11] * s1),
                           pack2(o[12] * s0, o[13] * s0), pack2(o[14] * s1, o[15] * s1));
            }
            fence_async_smem();
            __syncwarp();
            if (lane == 0) mbar_arrive(bar_od);
        }
        TL(tid == 128, 30);
        mainloop<2>(acc, nB - S2, ring, sbase, bar_full, bar_empty, wg, lane);
        TL(tid == 128, 7);
        {
            const float c0 = 1.f - __ldcg(&g_gate[grow]), c1 = 1.f - __ldcg(&g_gate[grow + 8]);
            const float b0 = kh ? __bfloat162float(prm.b2[grow]) : 0.f, b1v = kh ? __bfloat162float(prm.b2[grow + 8]) : 0.f;
#pragma unroll
            for (int i = 0; i < 32; i++) {
                acc[4 * i] = (acc[4 * i] + b0) * c0;
                acc[4 * i + 1] = (acc[4 * i + 1] + b0) * c0;
                acc[4 * i + 2] = (acc[4 * i + 2] + b1v) * c1;
                acc[4 * i + 3] = (acc[4 * i + 3] + b1v) * c1;
            }
        }
        mainloop<2>(acc, 512 / BK, ring, sbase, bar_full, bar_empty, wg, lane);
        TL(tid == 128, 8);
        if (kh == 0) {
            uint4* dst = &g_part[(size_t)(st * 4 + nt) * 16 * 256 + tid];
#pragma unroll
            for (int i = 0; i < 16; i++)
                dst[i * 256] = make_uint4(pack2(acc[8 * i], acc[8 * i + 1]), pack2(acc[8 * i + 2], acc[8 * i + 3]),
                                          pack2(acc[8 * i + 4], acc[8 * i + 5]), pack2(acc[8 * i + 6], acc[8 * i + 7]));
            fence_async_glob();
            bar_sync(2, 256);
            if (tid == 0) flag_add(&g_flags[(FL_PART + st * 4 + nt) * 32]);
        } else {
            mbar_wait<0>(bar_part, 0);
            TL(tid == 128, 10);
            bar_sync(2, 256);
            const uint32_t obase = sbase + wg * 32768 + (wq * 16 + lb3 * 8 + l7) * 128;
#pragma unroll
            for (int i = 0; i < 16; i++) {
                const uint4 pv = lds128(stg + (i * 256 + tid) * 16);
                const uint32_t addr = obase + (i >> 2) * 8192 + (((((2 * i) & 7) + lb4) ^ l7) << 4);
                stmatrix4(addr, pack2(acc[8 * i] + bf_lo(pv.x), acc[8 * i + 1] + bf_hi(pv.x)),
                          pack2(acc[8 * i + 2] + bf_lo(pv.y), acc[8 * i + 3] + bf_hi(pv.y)),
                          pack2(acc[8 * i + 4] + bf_lo(pv.z), acc[8 * i + 5] + bf_hi(pv.z)),
                          pack2(acc[8 * i + 6] + bf_lo(pv.w), acc[8 * i + 7] + bf_hi(pv.w)));
            }
            fence_async_smem();
            bar_sync(3 + wg, 128);
            if ((tid & 127) == 0) {
#pragma unroll
                for (int c = 0; c < 4; c++)
                    tma2d_store(&m_out, sbase + wg * 32768 + c * 8192, nt * 256 + c * 64, st * 128 + wg * 64);
                bulk_commit();
                bulk_wait_read();
            }
        }
        TL(tid == 128, 9);
        if (tid == 0) role_done();
    }
}

typedef CUresult (*EncodeFn)(CUtensorMap*, CUtensorMapDataType, cuuint32_t, void*, const cuuint64_t*, const cuuint64_t*,
                             const cuuint32_t*, const cuuint32_t*, CUtensorMapInterleave, CUtensorMapSwizzle,
                             CUtensorMapL2promotion, CUtensorMapFloatOOBfill);

void make_map(EncodeFn enc, CUtensorMap* m, const void* ptr, int rank, const uint64_t* dims, const uint64_t* strides_bytes,
              const uint32_t* box, CUtensorMapSwizzle swz) {
    cuuint64_t gd[3], gs[2];
    cuuint32_t bd[3], es[3] = {1, 1, 1};
    for (int i = 0; i < rank; i++) { gd[i] = dims[i]; bd[i] = box[i]; }
    for (int i = 0; i < rank - 1; i++) gs[i] = strides_bytes[i];
    CUresult res = enc(m, CU_TENSOR_MAP_DATA_TYPE_BFLOAT16, rank, const_cast<void*>(ptr), gd, gs, bd, es, CU_TENSOR_MAP_INTERLEAVE_NONE, swz,
        CU_TENSOR_MAP_L2_PROMOTION_L2_128B, CU_TENSOR_MAP_FLOAT_OOB_FILL_NONE);
    (void)res;
}

}

extern "C" void kernel_launch(void* const* d_in, const int* in_sizes, int n_in, void* d_out, int out_size) {
    (void)in_sizes; (void)n_in; (void)out_size;
    const __nv_bfloat16* x = (const __nv_bfloat16*)d_in[0];
    const __nv_bfloat16* wqkv = (const __nv_bfloat16*)d_in[1];
    const __nv_bfloat16* wphi = (const __nv_bfloat16*)d_in[2];
    const __nv_bfloat16* wo = (const __nv_bfloat16*)d_in[3];
    const __nv_bfloat16* w1 = (const __nv_bfloat16*)d_in[5];
    const __nv_bfloat16* b1 = (const __nv_bfloat16*)d_in[6];
    const __nv_bfloat16* w2 = (const __nv_bfloat16*)d_in[7];
    const __nv_bfloat16* b2 = (const __nv_bfloat16*)d_in[8];
    const __nv_bfloat16* gate_w = (const __nv_bfloat16*)d_in[9];

    EncodeFn enc = nullptr;
    cudaDriverEntryPointQueryResult qr;
    cudaGetDriverEntryPoint("cuTensorMapEncodeTiled", (void**)&enc, cudaEnableDefault, &qr);
    void *p_h, *p_u, *p_o;
    cudaGetSymbolAddress(&p_h, g_h);
    cudaGetSymbolAddress(&p_u, g_u);
    cudaGetSymbolAddress(&p_o, g_o);

    CUtensorMap m_x, m_wqkv, m_h, m_w1, m_w2, m_u, m_o, m_wo, m_os, m_out;
    {
        uint64_t d[3] = {1024, 2048, 1}, s[2] = {2048, 2048 * 2048};
        uint32_t b[3] = {BK, 128, 1};
        make_map(enc, &m_x, x, 3, d, s, b, BK == 64 ? CU_TENSOR_MAP_SWIZZLE_128B : CU_TENSOR_MAP_SWIZZLE_64B);
    }
    {
        uint64_t d[2] = {1024, 2048}, s[1] = {2048};
        uint32_t b[2] = {64, 64};
        make_map(enc, &m_out, d_out, 2, d, s, b, CU_TENSOR_MAP_SWIZZLE_128B);
    }
    {
        uint64_t d[3] = {1024, 1024, 3}, s[2] = {6144, 2048};
        uint32_t b[3] = {64, BK, 3};
        make_map(enc, &m_wqkv, wqkv, 3, d, s, b, CU_TENSOR_MAP_SWIZZLE_128B);
    }
    {
        uint64_t d[3] = {64, 2048, 16}, s[2] = {2048, 128};
        uint32_t b[3] = {64, BK, 2};
        make_map(enc, &m_h, p_h, 3, d, s, b, CU_TENSOR_MAP_SWIZZLE_128B);
    }
    {
        uint64_t d[3] = {32, 2048, 112}, s[2] = {7168, 64};
        uint32_t b[3] = {32, BK, 7};
        make_map(enc, &m_w1, w1, 3, d, s, b, CU_TENSOR_MAP_SWIZZLE_64B);
    }
    {
        uint64_t d[3] = {64, 3584, 32}, s[2] = {4096, 128};
        uint32_t b[3] = {64, BK, 2};
        make_map(enc, &m_w2, w2, 3, d, s, b, CU_TENSOR_MAP_SWIZZLE_128B);
    }
    {
        uint64_t d[3] = {64, 3584, 16}, s[2] = {2048, 128};
        uint32_t b[3] = {64, BK, 4};
        make_map(enc, &m_u, p_u, 3, d, s, b, CU_TENSOR_MAP_SWIZZLE_128B);
    }
    {
        uint64_t d[3] = {64, 1024, 32}, s[2] = {4096, 128};
        uint32_t b[3] = {64, BK, 2};
        make_map(enc, &m_o, p_o, 3, d, s, b, CU_TENSOR_MAP_SWIZZLE_128B);
        uint32_t bs[3] = {64, 64, 2};
        make_map(enc, &m_os, p_o, 3, d, s, bs, CU_TENSOR_MAP_SWIZZLE_128B);
    }
    {
        uint64_t d[3] = {64, 1024, 16}, s[2] = {2048, 128};
        uint32_t b[3] = {64, BK, 4};
        make_map(enc, &m_wo, wo, 3, d, s, b, CU_TENSOR_MAP_SWIZZLE_128B);
    }
    Params prm{x, wphi, b1, b2, gate_w};

    cudaFuncSetAttribute(fused_kernel, cudaFuncAttributeMaxDynamicSharedMemorySize, SMEM_BYTES);
    fused_kernel<<<NCTA, NTHREADS, SMEM_BYTES, cudaStreamPerThread>>>(m_x, m_wqkv, m_h, m_w1, m_w2, m_u, m_o, m_wo, m_os, m_out, prm);
}
```

```cpp
#include <cuda_runtime.h>
#include <cuda.h>
#include <cuda_bf16.h>
#include <stdint.h>

namespace {

constexpr int S_ = 2048, D_ = 1024, F_ = 3584;
constexpr int NCTA = 128;
#define BK_ 32
constexpr int BK = BK_;
constexpr int NSTAGE = 192 / BK;
constexpr int SLOT = BK * 768;
constexpr int BOFF = BK * 256;
constexpr int OFF_STG = NSTAGE * SLOT;
constexpr int OFF_WPHI = OFF_STG + 65536;
constexpr int OFF_BAR = OFF_WPHI + 8192;
constexpr int OFF_TAB = OFF_BAR + 256;
constexpr int SMEM_BYTES = OFF_TAB + 512 + 1024;
#define N0_ 28
constexpr int N0 = N0_ * (64 / BK);
constexpr int FB = F_ / BK;
constexpr int NTHREADS = 384;
#define GH_ 0
constexpr int GH = GH_;
#define S1_ 14
#define S2_ 20
constexpr int S1 = S1_ * (64 / BK), S2 = S2_ * (64 / BK);

constexpr int FL_LN = 0, FL_U = 1, FL_KV = 5, FL_O = 21, FL_PART = 37, FL_COUNT = 165;

__device__ __align__(1024) __nv_bfloat16 g_h[S_ * D_];
__device__ __align__(1024) __nv_bfloat16 g_u[F_ * D_];
__device__ __align__(1024) __nv_bfloat16 g_o[D_ * S_];
__device__ __align__(1024) uint4 g_pq[NCTA * 16 * 8 * 32];
__device__ __align__(1024) float4 g_kvsum[16 * 2 * 8 * 96];
__device__ __align__(1024) uint4 g_part[64 * 16 * 256];
__device__ __align__(1024) float g_gate[S_];
__device__ __align__(1024) unsigned g_flags[FL_COUNT * 32];

#define TL(cond, idx)
#define TR(cond, idx)
#define TLG(cond, idx)
__device__ __forceinline__ uint32_t smem_u32(const void* p) { return (uint32_t)__cvta_generic_to_shared(p); }
__device__ __forceinline__ void mbar_init(uint32_t bar, uint32_t cnt) {
    asm volatile("mbarrier.init.shared::cta.b64 [%0], %1;" ::"r"(bar), "r"(cnt));
}
__device__ __forceinline__ void mbar_expect_tx(uint32_t bar, uint32_t bytes) {
    asm volatile("mbarrier.arrive.expect_tx.shared::cta.b64 _, [%0], %1;" ::"r"(bar), "r"(bytes) : "memory");
}
__device__ __forceinline__ void mbar_arrive(uint32_t bar) {
    asm volatile("mbarrier.arrive.shared::cta.b64 _, [%0];" ::"r"(bar) : "memory");
}
template <int ROLE>
__device__ __forceinline__ void mbar_wait(uint32_t bar, uint32_t parity) {
    uint32_t done;
    int n = 0;
    while (true) {
        asm volatile("{\n.reg .pred p;\nmbarrier.try_wait.parity.shared::cta.b64 p, [%1], %2;\nselp.u32 %0, 1, 0, p;\n}"
                     : "=r"(done) : "r"(bar), "r"(parity) : "memory");
        if (done || ++n >= (1 << 16)) break;
    }
}
__device__ __forceinline__ bool mbar_test(uint32_t bar, uint32_t parity) {
    uint32_t done;
    asm volatile("{\n.reg .pred p;\nmbarrier.test_wait.parity.shared::cta.b64 p, [%1], %2;\nselp.u32 %0, 1, 0, p;\n}"
                 : "=r"(done) : "r"(bar), "r"(parity) : "memory");
    return done != 0;
}
__device__ __forceinline__ bool mbar_try(uint32_t bar, uint32_t parity, uint32_t ns) {
    uint32_t done;
    asm volatile("{\n.reg .pred p;\nmbarrier.try_wait.parity.shared::cta.b64 p, [%1], %2, %3;\nselp.u32 %0, 1, 0, p;\n}"
                 : "=r"(done) : "r"(bar), "r"(parity), "r"(ns) : "memory");
    return done != 0;
}
__device__ __forceinline__ unsigned ld_relaxed(const unsigned* p) {
    unsigned v;
    asm volatile("ld.relaxed.gpu.global.u32 %0, [%1];" : "=r"(v) : "l"(p) : "memory");
    return v;
}
template <int ROLE>
__device__ __forceinline__ void wait_flag(const unsigned* p, unsigned target, unsigned epoch) {
    unsigned v;
    int n = 0;
    const unsigned base = epoch * target;
    while (true) {
        asm volatile("ld.acquire.gpu.global.u32 %0, [%1];" : "=r"(v) : "l"(p) : "memory");
        if (v - base >= target) break;
        if (++n > (1 << 16)) break;
        __nanosleep(40);
    }
}
__device__ __forceinline__ void flag_add(unsigned* p) {
    asm volatile("red.release.gpu.global.add.u32 [%0], 1;" ::"l"(p) : "memory");
}
__device__ __forceinline__ void fence_async_smem() { asm volatile("fence.proxy.async.shared::cta;" ::: "memory"); }
__device__ __forceinline__ void fence_async_glob() { asm volatile("fence.proxy.async.global;" ::: "memory"); }
__device__ __forceinline__ void bar_sync(int id, int n) {
    __syncwarp();
    asm volatile("bar.sync %0, %1;" ::"r"(id), "r"(n) : "memory");
}

__device__ __forceinline__ void tma3d(uint32_t dst, const CUtensorMap* m, int c0, int c1, int c2, uint32_t bar) {
    asm volatile("cp.async.bulk.tensor.3d.shared::cluster.global.mbarrier::complete_tx::bytes [%0], [%1, {%3, %4, %5}], [%2];"
                 ::"r"(dst), "l"((uint64_t)m), "r"(bar), "r"(c0), "r"(c1), "r"(c2) : "memory");
}
__device__ __forceinline__ void tma2d_store(const CUtensorMap* m, uint32_t src, int c0, int c1) {
    asm volatile("cp.async.bulk.tensor.2d.global.shared::cta.bulk_group [%0, {%2, %3}], [%1];"
                 ::"l"((uint64_t)m), "r"(src), "r"(c0), "r"(c1) : "memory");
}
__device__ __forceinline__ void tma3d_store(const CUtensorMap* m, uint32_t src, int c0, int c1, int c2) {
    asm volatile("cp.async.bulk.tensor.3d.global.shared::cta.bulk_group [%0, {%2, %3, %4}], [%1];"
                 ::"l"((uint64_t)m), "r"(src), "r"(c0), "r"(c1), "r"(c2) : "memory");
}
__device__ __forceinline__ void tma3d_prefetch(const CUtensorMap* m, int c0, int c1, int c2) {
    asm volatile("cp.async.bulk.prefetch.tensor.3d.L2.global [%0, {%1, %2, %3}];" ::"l"((uint64_t)m), "r"(c0), "r"(c1), "r"(c2) : "memory");
}
__device__ __forceinline__ void bulk_prefetch_l2(const void* src, uint32_t bytes) {
    asm volatile("cp.async.bulk.prefetch.L2.global [%0], %1;" ::"l"((uint64_t)src), "r"(bytes) : "memory");
}
__device__ __forceinline__ void bulk_load(uint32_t dst, const void* src, uint32_t bytes, uint32_t bar) {
    asm volatile("cp.async.bulk.shared::cluster.global.mbarrier::complete_tx::bytes [%0], [%1], %2, [%3];"
                 ::"r"(dst), "l"((uint64_t)src), "r"(bytes), "r"(bar) : "memory");
}
__device__ __forceinline__ void bulk_commit() { asm volatile("cp.async.bulk.commit_group;" ::: "memory"); }
__device__ __forceinline__ void bulk_wait_all() { asm volatile("cp.async.bulk.wait_group 0;" ::: "memory"); }
__device__ __forceinline__ void bulk_wait_read() { asm volatile("cp.async.bulk.wait_group.read 0;" ::: "memory"); }

__device__ __forceinline__ void wgmma_fence() { asm volatile("wgmma.fence.sync.aligned;" ::: "memory"); }
__device__ __forceinline__ void wgmma_commit() { asm volatile("wgmma.commit_group.sync.aligned;" ::: "memory"); }
template <int N>
__device__ __forceinline__ void wgmma_wait() { asm volatile("wgmma.wait_group.sync.aligned %0;" ::"n"(N) : "memory"); }

__device__ __forceinline__ uint64_t mkdesc(uint32_t addr, uint32_t lbo, uint32_t sbo, uint32_t swz) {
    return (uint64_t)((addr & 0x3FFFF) >> 4) | ((uint64_t)(lbo >> 4) << 16) | ((uint64_t)(sbo >> 4) << 32) | ((uint64_t)swz << 62);
}
__device__ __forceinline__ uint32_t pack2(float lo, float hi) {
    uint32_t r;
    asm("cvt.rn.bf16x2.f32 %0, %1, %2;" : "=r"(r) : "f"(hi), "f"(lo));
    return r;
}
__device__ __forceinline__ float bf_lo(uint32_t v) { return __uint_as_float(v << 16); }
__device__ __forceinline__ float bf_hi(uint32_t v) { return __uint_as_float(v & 0xFFFF0000u); }
__device__ __forceinline__ void stmatrix4(uint32_t addr, uint32_t r0, uint32_t r1, uint32_t r2, uint32_t r3) {
    asm volatile("stmatrix.sync.aligned.m8n8.x4.shared.b16 [%0], {%1, %2, %3, %4};" ::"r"(addr), "r"(r0), "r"(r1), "r"(r2), "r"(r3) : "memory");
}
__device__ __forceinline__ void stmatrix4t(uint32_t addr, uint32_t r0, uint32_t r1, uint32_t r2, uint32_t r3) {
    asm volatile("stmatrix.sync.aligned.m8n8.x4.trans.shared.b16 [%0], {%1, %2, %3, %4};" ::"r"(addr), "r"(r0), "r"(r1), "r"(r2), "r"(r3) : "memory");
}
__device__ __forceinline__ void ldsm4(uint32_t addr, uint32_t& r0, uint32_t& r1, uint32_t& r2, uint32_t& r3) {
    asm volatile("ldmatrix.sync.aligned.m8n8.x4.shared.b16 {%0, %1, %2, %3}, [%4];" : "=r"(r0), "=r"(r1), "=r"(r2), "=r"(r3) : "r"(addr) : "memory");
}
__device__ __forceinline__ uint4 lds128(uint32_t addr) {
    uint4 v;
    asm volatile("ld.shared.v4.u32 {%0, %1, %2, %3}, [%4];" : "=r"(v.x), "=r"(v.y), "=r"(v.z), "=r"(v.w) : "r"(addr) : "memory");
    return v;
}
__device__ __forceinline__ void sts128(uint32_t addr, uint4 v) {
    asm volatile("st.shared.v4.u32 [%0], {%1, %2, %3, %4};" ::"r"(addr), "r"(v.x), "r"(v.y), "r"(v.z), "r"(v.w) : "memory");
}
__device__ __forceinline__ void sts32(uint32_t addr, uint32_t v) {
    asm volatile("st.shared.u32 [%0], %1;" ::"r"(addr), "r"(v) : "memory");
}
__device__ __forceinline__ float ex2(float x) {
    float r;
    asm("ex2.approx.ftz.f32 %0, %1;" : "=f"(r) : "f"(x));
    return r;
}
__device__ __forceinline__ float rcp_fast(float x) {
    float r;
    asm("rcp.approx.ftz.f32 %0, %1;" : "=f"(r) : "f"(x));
    return r;
}
__device__ __forceinline__ void red_add4(float4* p, float4 v) {
    asm volatile("red.relaxed.gpu.global.add.v4.f32 [%0], {%1, %2, %3, %4};" ::"l"(p), "f"(v.x), "f"(v.y), "f"(v.z), "f"(v.w) : "memory");
}
__device__ __forceinline__ float tanh_fast(float x) {
    float r;
    asm("tanh.approx.f32 %0, %1;" : "=f"(r) : "f"(x));
    return r;
}
__device__ __forceinline__ float gelu_tanh(float u) {
    const float z = u * fmaf(u * u, 0.7978845608028654f * 0.044715f, 0.7978845608028654f);
    const float hu = 0.5f * u;
    return fmaf(hu, tanh_fast(z), hu);
}

template <int N>
__device__ __forceinline__ void zero(float (&a)[N]) {
#pragma unroll
    for (int i = 0; i < N; i++) a[i] = 0.f;
}

template <int N>
__device__ __forceinline__ void pin(float (&a)[N]) {
#pragma unroll
    for (int i = 0; i < N; i++) asm volatile("" : "+f"(a[i])::"memory");
}
__device__ __forceinline__ void pin(uint32_t& a) { asm volatile("" : "+r"(a)::"memory"); }

template <int TA, int TB>
__device__ __forceinline__ void wgmma_n192(float (&d)[96], uint64_t da, uint64_t db, int scale_d) {
    asm volatile("{\n.reg .pred p;\nsetp.ne.b32 p, %98, 0;\n"
        "wgmma.mma_async.sync.aligned.m64n192k16.f32.bf16.bf16 {%0, %1, %2, %3, %4, %5, %6, %7, %8, %9, %10, %11, %12, %13, %14, %15, %16, %17, %18, %19, %20, %21, %22, %23, %24, %25, %26, %27, %28, %29, %30, %31, %32, %33, %34, %35, %36, %37, %38, %39, %40, %41, %42, %43, %44, %45, %46, %47, %48, %49, %50, %51, %52, %53, %54, %55, %56, %57, %58, %59, %60, %61, %62, %63, %64, %65, %66, %67, %68, %69, %70, %71, %72, %73, %74, %75, %76, %77, %78, %79, %80, %81, %82, %83, %84, %85, %86, %87, %88, %89, %90, %91, %92, %93, %94, %95}, %96, %97, p, 1, 1, %99, %100;\n}\n"
        : "+f"(d[0]), "+f"(d[1]), "+f"(d[2]), "+f"(d[3]), "+f"(d[4]), "+f"(d[5]), "+f"(d[6]), "+f"(d[7]), "+f"(d[8]), "+f"(d[9]), "+f"(d[10]), "+f"(d[11]), "+f"(d[12]), "+f"(d[13]), "+f"(d[14]), "+f"(d[15]), "+f"(d[16]), "+f"(d[17]), "+f"(d[18]), "+f"(d[19]), "+f"(d[20]), "+f"(d[21]), "+f"(d[22]), "+f"(d[23]), "+f"(d[24]), "+f"(d[25]), "+f"(d[26]), "+f"(d[27]), "+f"(d[28]), "+f"(d[29]), "+f"(d[30]), "+f"(d[31]), "+f"(d[32]), "+f"(d[33]), "+f"(d[34]), "+f"(d[35]), "+f"(d[36]), "+f"(d[37]), "+f"(d[38]), "+f"(d[39]), "+f"(d[40]), "+f"(d[41]), "+f"(d[42]), "+f"(d[43]), "+f"(d[44]), "+f"(d[45]), "+f"(d[46]), "+f"(d[47]), "+f"(d[48]), "+f"(d[49]), "+f"(d[50]), "+f"(d[51]), "+f"(d[52]), "+f"(d[53]), "+f"(d[54]), "+f"(d[55]), "+f"(d[56]), "+f"(d[57]), "+f"(d[58]), "+f"(d[59]), "+f"(d[60]), "+f"(d[61]), "+f"(d[62]), "+f"(d[63]), "+f"(d[64]), "+f"(d[65]), "+f"(d[66]), "+f"(d[67]), "+f"(d[68]), "+f"(d[69]), "+f"(d[70]), "+f"(d[71]), "+f"(d[72]), "+f"(d[73]), "+f"(d[74]), "+f"(d[75]), "+f"(d[76]), "+f"(d[77]), "+f"(d[78]), "+f"(d[79]), "+f"(d[80]), "+f"(d[81]), "+f"(d[82]), "+f"(d[83]), "+f"(d[84]), "+f"(d[85]), "+f"(d[86]), "+f"(d[87]), "+f"(d[88]), "+f"(d[89]), "+f"(d[90]), "+f"(d[91]), "+f"(d[92]), "+f"(d[93]), "+f"(d[94]), "+f"(d[95])
        : "l"(da), "l"(db), "r"(scale_d), "n"(TA), "n"(TB));
}
template <int TA, int TB>
__device__ __forceinline__ void wgmma_n224(float (&d)[112], uint64_t da, uint64_t db, int scale_d) {
    asm volatile("{\n.reg .pred p;\nsetp.ne.b32 p, %114, 0;\n"
        "wgmma.mma_async.sync.aligned.m64n224k16.f32.bf16.bf16 {%0, %1, %2, %3, %4, %5, %6, %7, %8, %9, %10, %11, %12, %13, %14, %15, %16, %17, %18, %19, %20, %21, %22, %23, %24, %25, %26, %27, %28, %29, %30, %31, %32, %33, %34, %35, %36, %37, %38, %39, %40, %41, %42, %43, %44, %45, %46, %47, %48, %49, %50, %51, %52, %53, %54, %55, %56, %57, %58, %59, %60, %61, %62, %63, %64, %65, %66, %67, %68, %69, %70, %71, %72, %73, %74, %75, %76, %77, %78, %79, %80, %81, %82, %83, %84, %85, %86, %87, %88, %89, %90, %91, %92, %93, %94, %95, %96, %97, %98, %99, %100, %101, %102, %103, %104, %105, %106, %107, %108, %109, %110, %111}, %112, %113, p, 1, 1, %115, %116;\n}\n"
        : "+f"(d[0]), "+f"(d[1]), "+f"(d[2]), "+f"(d[3]), "+f"(d[4]), "+f"(d[5]), "+f"(d[6]), "+f"(d[7]), "+f"(d[8]), "+f"(d[9]), "+f"(d[10]), "+f"(d[11]), "+f"(d[12]), "+f"(d[13]), "+f"(d[14]), "+f"(d[15]), "+f"(d[16]), "+f"(d[17]), "+f"(d[18]), "+f"(d[19]), "+f"(d[20]), "+f"(d[21]), "+f"(d[22]), "+f"(d[23]), "+f"(d[24]), "+f"(d[25]), "+f"(d[26]), "+f"(d[27]), "+f"(d[28]), "+f"(d[29]), "+f"(d[30]), "+f"(d[31]), "+f"(d[32]), "+f"(d[33]), "+f"(d[34]), "+f"(d[35]), "+f"(d[36]), "+f"(d[37]), "+f"(d[38]), "+f"(d[39]), "+f"(d[40]), "+f"(d[41]), "+f"(d[42]), "+f"(d[43]), "+f"(d[44]), "+f"(d[45]), "+f"(d[46]), "+f"(d[47]), "+f"(d[48]), "+f"(d[49]), "+f"(d[50]), "+f"(d[51]), "+f"(d[52]), "+f"(d[53]), "+f"(d[54]), "+f"(d[55]), "+f"(d[56]), "+f"(d[57]), "+f"(d[58]), "+f"(d[59]), "+f"(d[60]), "+f"(d[61]), "+f"(d[62]), "+f"(d[63]), "+f"(d[64]), "+f"(d[65]), "+f"(d[66]), "+f"(d[67]), "+f"(d[68]), "+f"(d[69]), "+f"(d[70]), "+f"(d[71]), "+f"(d[72]), "+f"(d[73]), "+f"(d[74]), "+f"(d[75]), "+f"(d[76]), "+f"(d[77]), "+f"(d[78]), "+f"(d[79]), "+f"(d[80]), "+f"(d[81]), "+f"(d[82]), "+f"(d[83]), "+f"(d[84]), "+f"(d[85]), "+f"(d[86]), "+f"(d[87]), "+f"(d[88]), "+f"(d[89]), "+f"(d[90]), "+f"(d[91]), "+f"(d[92]), "+f"(d[93]), "+f"(d[94]), "+f"(d[95]), "+f"(d[96]), "+f"(d[97]), "+f"(d[98]), "+f"(d[99]), "+f"(d[100]), "+f"(d[101]), "+f"(d[102]), "+f"(d[103]), "+f"(d[104]), "+f"(d[105]), "+f"(d[106]), "+f"(d[107]), "+f"(d[108]), "+f"(d[109]), "+f"(d[110]), "+f"(d[111])
        : "l"(da), "l"(db), "r"(scale_d), "n"(TA), "n"(TB));
}
template <int TA, int TB>
__device__ __forceinline__ void wgmma_n256(float (&d)[128], uint64_t da, uint64_t db, int scale_d) {
    asm volatile("{\n.reg .pred p;\nsetp.ne.b32 p, %130, 0;\n"
        "wgmma.mma_async.sync.aligned.m64n256k16.f32.bf16.bf16 {%0, %1, %2, %3, %4, %5, %6, %7, %8, %9, %10, %11, %12, %13, %14, %15, %16, %17, %18, %19, %20, %21, %22, %23, %24, %25, %26, %27, %28, %29, %30, %31, %32, %33, %34, %35, %36, %37, %38, %39, %40, %41, %42, %43, %44, %45, %46, %47, %48, %49, %50, %51, %52, %53, %54, %55, %56, %57, %58, %59, %60, %61, %62, %63, %64, %65, %66, %67, %68, %69, %70, %71, %72, %73, %74, %75, %76, %77, %78, %79, %80, %81, %82, %83, %84, %85, %86, %87, %88, %89, %90, %91, %92, %93, %94, %95, %96, %97, %98, %99, %100, %101, %102, %103, %104, %105, %106, %107, %108, %109, %110, %111, %112, %113, %114, %115, %116, %117, %118, %119, %120, %121, %122, %123, %124, %125, %126, %127}, %128, %129, p, 1, 1, %131, %132;\n}\n"
        : "+f"(d[0]), "+f"(d[1]), "+f"(d[2]), "+f"(d[3]), "+f"(d[4]), "+f"(d[5]), "+f"(d[6]), "+f"(d[7]), "+f"(d[8]), "+f"(d[9]), "+f"(d[10]), "+f"(d[11]), "+f"(d[12]), "+f"(d[13]), "+f"(d[14]), "+f"(d[15]), "+f"(d[16]), "+f"(d[17]), "+f"(d[18]), "+f"(d[19]), "+f"(d[20]), "+f"(d[21]), "+f"(d[22]), "+f"(d[23]), "+f"(d[24]), "+f"(d[25]), "+f"(d[26]), "+f"(d[27]), "+f"(d[28]), "+f"(d[29]), "+f"(d[30]), "+f"(d[31]), "+f"(d[32]), "+f"(d[33]), "+f"(d[34]), "+f"(d[35]), "+f"(d[36]), "+f"(d[37]), "+f"(d[38]), "+f"(d[39]), "+f"(d[40]), "+f"(d[41]), "+f"(d[42]), "+f"(d[43]), "+f"(d[44]), "+f"(d[45]), "+f"(d[46]), "+f"(d[47]), "+f"(d[48]), "+f"(d[49]), "+f"(d[50]), "+f"(d[51]), "+f"(d[52]), "+f"(d[53]), "+f"(d[54]), "+f"(d[55]), "+f"(d[56]), "+f"(d[57]), "+f"(d[58]), "+f"(d[59]), "+f"(d[60]), "+f"(d[61]), "+f"(d[62]), "+f"(d[63]), "+f"(d[64]), "+f"(d[65]), "+f"(d[66]), "+f"(d[67]), "+f"(d[68]), "+f"(d[69]), "+f"(d[70]), "+f"(d[71]), "+f"(d[72]), "+f"(d[73]), "+f"(d[74]), "+f"(d[75]), "+f"(d[76]), "+f"(d[77]), "+f"(d[78]), "+f"(d[79]), "+f"(d[80]), "+f"(d[81]), "+f"(d[82]), "+f"(d[83]), "+f"(d[84]), "+f"(d[85]), "+f"(d[86]), "+f"(d[87]), "+f"(d[88]), "+f"(d[89]), "+f"(d[90]), "+f"(d[91]), "+f"(d[92]), "+f"(d[93]), "+f"(d[94]), "+f"(d[95]), "+f"(d[96]), "+f"(d[97]), "+f"(d[98]), "+f"(d[99]), "+f"(d[100]), "+f"(d[101]), "+f"(d[102]), "+f"(d[103]), "+f"(d[104]), "+f"(d[105]), "+f"(d[106]), "+f"(d[107]), "+f"(d[108]), "+f"(d[109]), "+f"(d[110]), "+f"(d[111]), "+f"(d[112]), "+f"(d[113]), "+f"(d[114]), "+f"(d[115]), "+f"(d[116]), "+f"(d[117]), "+f"(d[118]), "+f"(d[119]), "+f"(d[120]), "+f"(d[121]), "+f"(d[122]), "+f"(d[123]), "+f"(d[124]), "+f"(d[125]), "+f"(d[126]), "+f"(d[127])
        : "l"(da), "l"(db), "r"(scale_d), "n"(TA), "n"(TB));
}
template <int TA, int TB>
__device__ __forceinline__ void wgmma_n64(float (&d)[32], uint64_t da, uint64_t db, int scale_d) {
    asm volatile("{\n.reg .pred p;\nsetp.ne.b32 p, %34, 0;\n"
        "wgmma.mma_async.sync.aligned.m64n64k16.f32.bf16.bf16 {%0, %1, %2, %3, %4, %5, %6, %7, %8, %9, %10, %11, %12, %13, %14, %15, %16, %17, %18, %19, %20, %21, %22, %23, %24, %25, %26, %27, %28, %29, %30, %31}, %32, %33, p, 1, 1, %35, %36;\n}\n"
        : "+f"(d[0]), "+f"(d[1]), "+f"(d[2]), "+f"(d[3]), "+f"(d[4]), "+f"(d[5]), "+f"(d[6]), "+f"(d[7]), "+f"(d[8]), "+f"(d[9]), "+f"(d[10]), "+f"(d[11]), "+f"(d[12]), "+f"(d[13]), "+f"(d[14]), "+f"(d[15]), "+f"(d[16]), "+f"(d[17]), "+f"(d[18]), "+f"(d[19]), "+f"(d[20]), "+f"(d[21]), "+f"(d[22]), "+f"(d[23]), "+f"(d[24]), "+f"(d[25]), "+f"(d[26]), "+f"(d[27]), "+f"(d[28]), "+f"(d[29]), "+f"(d[30]), "+f"(d[31])
        : "l"(da), "l"(db), "r"(scale_d), "n"(TA), "n"(TB));
}
template <int TB>
__device__ __forceinline__ void wgmma_rs_n32(float (&d)[16], uint32_t a0, uint32_t a1, uint32_t a2, uint32_t a3, uint64_t db, int scale_d) {
    asm volatile("{\n.reg .pred p;\nsetp.ne.b32 p, %21, 0;\n"
        "wgmma.mma_async.sync.aligned.m64n32k16.f32.bf16.bf16 {%0, %1, %2, %3, %4, %5, %6, %7, %8, %9, %10, %11, %12, %13, %14, %15}, {%16, %17, %18, %19}, %20, p, 1, 1, %22;\n}\n"
        : "+f"(d[0]), "+f"(d[1]), "+f"(d[2]), "+f"(d[3]), "+f"(d[4]), "+f"(d[5]), "+f"(d[6]), "+f"(d[7]), "+f"(d[8]), "+f"(d[9]), "+f"(d[10]), "+f"(d[11]), "+f"(d[12]), "+f"(d[13]), "+f"(d[14]), "+f"(d[15])
        : "r"(a0), "r"(a1), "r"(a2), "r"(a3), "l"(db), "r"(scale_d), "n"(TB));
}
template <int TB>
__device__ __forceinline__ void wgmma_rs_n40(float (&d)[20], uint32_t a0, uint32_t a1, uint32_t a2, uint32_t a3, uint64_t db, int scale_d) {
    asm volatile("{\n.reg .pred p;\nsetp.ne.b32 p, %25, 0;\n"
        "wgmma.mma_async.sync.aligned.m64n40k16.f32.bf16.bf16 {%0, %1, %2, %3, %4, %5, %6, %7, %8, %9, %10, %11, %12, %13, %14, %15, %16, %17, %18, %19}, {%20, %21, %22, %23}, %24, p, 1, 1, %26;\n}\n"
        : "+f"(d[0]), "+f"(d[1]), "+f"(d[2]), "+f"(d[3]), "+f"(d[4]), "+f"(d[5]), "+f"(d[6]), "+f"(d[7]), "+f"(d[8]), "+f"(d[9]), "+f"(d[10]), "+f"(d[11]), "+f"(d[12]), "+f"(d[13]), "+f"(d[14]), "+f"(d[15]), "+f"(d[16]), "+f"(d[17]), "+f"(d[18]), "+f"(d[19])
        : "r"(a0), "r"(a1), "r"(a2), "r"(a3), "l"(db), "r"(scale_d), "n"(TB));
}

struct Ring {
    uint32_t s, ph;
    __device__ __forceinline__ void next() {
        if (++s == NSTAGE) { s = 0; ph ^= 1; }
    }
};

template <int MODE, int NACC>
__device__ __forceinline__ void mainloop(float (&acc)[NACC], int nkb, Ring& ring, uint32_t sbase, uint32_t bar_full,
                                         uint32_t bar_empty, int wg, int lane) {
    uint32_t prev_s = 0;
#pragma unroll 1
    for (int kb = 0; kb < nkb; kb++) {
        const uint32_t slot = sbase + ring.s * SLOT;
        TR(threadIdx.x == 128 && kb < 64, MODE * 64 + kb);
        mbar_wait<0>(bar_full + 8 * ring.s, ring.ph);
        wgmma_fence();
#pragma unroll
        for (int j = 0; j < BK / 16; j++) {
            if constexpr (MODE == 0) {
                wgmma_n192<0, 1>(acc, mkdesc(slot + wg * (BK * 128) + j * 32, 16, BK * 16, BK == 64 ? 1 : 2), mkdesc(slot + BOFF + j * 2048, BK * 128, 1024, 1), 1);
            } else if constexpr (MODE == 1) {
                wgmma_n224<1, 1>(acc, mkdesc(slot + wg * (BK * 128) + j * 2048, BK * 128, 1024, 1), mkdesc(slot + BOFF + j * 1024, BK * 64, 512, 2), 1);
            } else {
                wgmma_n256<1, 1>(acc, mkdesc(slot + wg * (BK * 128) + j * 2048, BK * 128, 1024, 1), mkdesc(slot + BOFF + j * 2048, BK * 128, 1024, 1), 1);
            }
        }
        wgmma_commit();
        if (kb > 0) {
            wgmma_wait<1>();
            if (lane == 0) mbar_arrive(bar_empty + 8 * prev_s);
        }
        prev_s = ring.s;
        ring.next();
    }
    wgmma_wait<0>();
    if (lane == 0) mbar_arrive(bar_empty + 8 * prev_s);
}

template <int NC>
__device__ __forceinline__ void dual_softmax(const uint32_t (&pk)[NC][4], uint32_t (&P)[NC][4], uint32_t (&M)[NC][4]) {
    constexpr float L2E = 1.4426950408889634f;
    uint32_t mm[NC];
#pragma unroll
    for (int c = 0; c < NC; c++) {
        __nv_bfloat162 a0 = *(const __nv_bfloat162*)&pk[c][0], a1 = *(const __nv_bfloat162*)&pk[c][1];
        __nv_bfloat162 a2 = *(const __nv_bfloat162*)&pk[c][2], a3 = *(const __nv_bfloat162*)&pk[c][3];
        __nv_bfloat162 mx = __hmax2(__hmax2(a0, a1), __hmax2(a2, a3));
        __nv_bfloat162 mn = __hmin2(__hmin2(a0, a1), __hmin2(a2, a3));
        const uint32_t umx = *(const uint32_t*)&mx, umn = (*(const uint32_t*)&mn) ^ 0x80008000u;
        const uint32_t lo = __byte_perm(umx, umn, 0x5410), hi = __byte_perm(umx, umn, 0x7632);
        __nv_bfloat162 r = __hmax2(*(const __nv_bfloat162*)&lo, *(const __nv_bfloat162*)&hi);
        mm[c] = *(const uint32_t*)&r;
    }
#pragma unroll
    for (int o = 1; o <= 2; o <<= 1) {
        uint32_t t[NC];
#pragma unroll
        for (int c = 0; c < NC; c++) t[c] = __shfl_xor_sync(0xffffffffu, mm[c], o);
#pragma unroll
        for (int c = 0; c < NC; c++) {
            __nv_bfloat162 r = __hmax2(*(const __nv_bfloat162*)&mm[c], *(const __nv_bfloat162*)&t[c]);
            mm[c] = *(const uint32_t*)&r;
        }
    }
    float ep[NC][8], em[NC][8], sp[NC], sm[NC];
#pragma unroll
    for (int c = 0; c < NC; c++) {
        const float mxs = bf_lo(mm[c]) * L2E, mns = bf_hi(mm[c]) * L2E;
#pragma unroll
        for (int i = 0; i < 4; i++) {
            const float a = bf_lo(pk[c][i]), b = bf_hi(pk[c][i]);
            ep[c][2 * i] = ex2(fmaf(a, L2E, -mxs));
            ep[c][2 * i + 1] = ex2(fmaf(b, L2E, -mxs));
            em[c][2 * i] = ex2(fmaf(a, -L2E, -mns));
            em[c][2 * i + 1] = ex2(fmaf(b, -L2E, -mns));
        }
        sp[c] = ((ep[c][0] + ep[c][1]) + (ep[c][2] + ep[c][3])) + ((ep[c][4] + ep[c][5]) + (ep[c][6] + ep[c][7]));
        sm[c] = ((em[c][0] + em[c][1]) + (em[c][2] + em[c][3])) + ((em[c][4] + em[c][5]) + (em[c][6] + em[c][7]));
    }
#pragma unroll
    for (int o = 1; o <= 2; o <<= 1) {
        float tp[NC], tm[NC];
#pragma unroll
        for (int c = 0; c < NC; c++) {
            tp[c] = __shfl_xor_sync(0xffffffffu, sp[c], o);
            tm[c] = __shfl_xor_sync(0xffffffffu, sm[c], o);
        }
#pragma unroll
        for (int c = 0; c < NC; c++) { sp[c] += tp[c]; sm[c] += tm[c]; }
    }
#pragma unroll
    for (int c = 0; c < NC; c++) {
        const float rp = rcp_fast(sp[c]), rm = rcp_fast(sm[c]);
#pragma unroll
        for (int i = 0; i < 4; i++) {
            P[c][i] = pack2(ep[c][2 * i] * rp, ep[c][2 * i + 1] * rp);
            M[c][i] = pack2(em[c][2 * i] * rm, em[c][2 * i + 1] * rm);
        }
    }
}

template <int NR>
__device__ __forceinline__ void ln_rows(const __nv_bfloat16* x, const __nv_bfloat16* gate_w, int row0, int row_end, int lane) {
    uint4 v[NR][4];
    float sh[NR], red[NR][3];
#pragma unroll
    for (int h = 0; h < NR; h++) {
        const int row = min(row0 + h, row_end - 1);
#pragma unroll
        for (int c = 0; c < 4; c++) v[h][c] = __ldg((const uint4*)(x + (size_t)row * D_) + c * 32 + lane);
        sh[h] = __bfloat162float(__ldg(x + (size_t)row * D_));
        red[h][0] = red[h][1] = red[h][2] = 0.f;
    }
#pragma unroll
    for (int c = 0; c < 4; c++) {
        const uint4 gw = __ldg((const uint4*)gate_w + c * 32 + lane);
        const uint32_t q[4] = {gw.x, gw.y, gw.z, gw.w};
#pragma unroll
        for (int h = 0; h < NR; h++) {
            const uint32_t w[4] = {v[h][c].x, v[h][c].y, v[h][c].z, v[h][c].w};
            float s0 = 0.f, q0 = 0.f, d0 = 0.f;
#pragma unroll
            for (int k = 0; k < 4; k++) {
                const float a = bf_lo(w[k]) - sh[h], b = bf_hi(w[k]) - sh[h];
                s0 += a + b;
                q0 = fmaf(a, a, fmaf(b, b, q0));
                d0 = fmaf(bf_lo(w[k]), bf_lo(q[k]), fmaf(bf_hi(w[k]), bf_hi(q[k]), d0));
            }
            red[h][0] += s0; red[h][1] += q0; red[h][2] += d0;
        }
    }
#pragma unroll
    for (int o = 16; o > 0; o >>= 1) {
        float t[NR][3];
#pragma unroll
        for (int h = 0; h < NR; h++)
#pragma unroll
            for (int k = 0; k < 3; k++) t[h][k] = __shfl_xor_sync(0xffffffffu, red[h][k], o);
#pragma unroll
        for (int h = 0; h < NR; h++)
#pragma unroll
            for (int k = 0; k < 3; k++) red[h][k] += t[h][k];
    }
#pragma unroll
    for (int h = 0; h < NR; h++) {
        if (row0 + h < row_end) {
            const float ms = red[h][0] * (1.f / D_);
            const float var = fmaxf(red[h][1] * (1.f / D_) - ms * ms, 0.f);
            const float rstd = rsqrtf(var + 1e-5f);
            const float nm = -(ms + sh[h]) * rstd;
            uint4* hr = (uint4*)(g_h + (size_t)(row0 + h) * D_) + lane;
#pragma unroll
            for (int c = 0; c < 4; c++) {
                uint4 o;
                o.x = pack2(fmaf(bf_lo(v[h][c].x), rstd, nm), fmaf(bf_hi(v[h][c].x), rstd, nm));
                o.y = pack2(fmaf(bf_lo(v[h][c].y), rstd, nm), fmaf(bf_hi(v[h][c].y), rstd, nm));
                o.z = pack2(fmaf(bf_lo(v[h][c].z), rstd, nm), fmaf(bf_hi(v[h][c].z), rstd, nm));
                o.w = pack2(fmaf(bf_lo(v[h][c].w), rstd, nm), fmaf(bf_hi(v[h][c].w), rstd, nm));
                hr[c * 32] = o;
            }
            if (lane == 0) g_gate[row0 + h] = 1.f / (1.f + __expf(-red[h][2]));
        }
    }
}

struct Params {
    const __nv_bfloat16* x;
    const __nv_bfloat16* wphi;
    const __nv_bfloat16* b1;
    const __nv_bfloat16* b2;
    const __nv_bfloat16* gate_w;
};

__global__ void __launch_bounds__(NTHREADS, 1)
fused_kernel(const __grid_constant__ CUtensorMap m_x, const __grid_constant__ CUtensorMap m_wqkv,
             const __grid_constant__ CUtensorMap m_h, const __grid_constant__ CUtensorMap m_w1,
             const __grid_constant__ CUtensorMap m_w2, const __grid_constant__ CUtensorMap m_u,
             const __grid_constant__ CUtensorMap m_o, const __grid_constant__ CUtensorMap m_wo,
             const __grid_constant__ CUtensorMap m_os, const __grid_constant__ CUtensorMap m_out, const Params prm) {
    extern __shared__ uint8_t smem_raw[];
    const uint32_t sbase = (smem_u32(smem_raw) + 1023u) & ~1023u;
    const uint32_t bar_full = sbase + OFF_BAR;
    const uint32_t bar_empty = bar_full + 8 * NSTAGE;
    const uint32_t bar_stg_full = bar_empty + 8 * NSTAGE;
    const uint32_t bar_stg_empty = bar_stg_full + 8;
    const uint32_t bar_part = bar_stg_empty + 8;
    const uint32_t bar_w = bar_part + 8;
    const uint32_t bar_ln = bar_w + 8;
    const uint32_t bar_phi = bar_ln + 8;
    const uint32_t bar_kvd = bar_phi + 8;
    const uint32_t bar_kvx = bar_kvd + 8;
    const uint32_t bar_od = bar_kvx + 8;
    const uint32_t stg = sbase + OFF_STG;

    const int tid = threadIdx.x;
    const int warp = tid >> 5, lane = tid & 31;
    const int cta = blockIdx.x;
    const int r = cta & 1, p = cta >> 1;
    const int hp = p & 15, tg = p >> 4;
    const int tok_a = tg * 4 + r, tok_b = tg * 4 + 2 + r;
    const int ft = p & 15, dt = (p >> 4) * 2 + r;
    const int st = (p & 7) * 2 + r, nt = (p >> 3) & 3, kh = p >> 5;
    const int nB = kh ? FB - N0 : N0;
    const int l7 = lane & 7, lb3 = (lane >> 3) & 1, lb4 = lane >> 4;
    const unsigned epoch = ld_relaxed(&g_flags[FL_LN * 32]) / NCTA;

    if (tid == 32) {
        asm volatile("prefetch.tensormap [%0];" ::"l"((uint64_t)&m_x) : "memory");
        asm volatile("prefetch.tensormap [%0];" ::"l"((uint64_t)&m_wqkv) : "memory");
        asm volatile("prefetch.tensormap [%0];" ::"l"((uint64_t)&m_h) : "memory");
        asm volatile("prefetch.tensormap [%0];" ::"l"((uint64_t)&m_w1) : "memory");
    }
    if (tid == 256) {
        for (int i = 0; i < NSTAGE; i++) {
            mbar_init(bar_full + 8 * i, 1);
            mbar_init(bar_empty + 8 * i, 8);
        }
        mbar_init(bar_stg_full, 8);
        mbar_init(bar_stg_empty, 1);
        mbar_init(bar_part, 1);
        mbar_init(bar_w, 1);
        mbar_init(bar_ln, 8);
        mbar_init(bar_phi, 1);
        mbar_init(bar_kvd, 8);
        mbar_init(bar_kvx, 1);
        mbar_init(bar_od, 8);
        fence_async_smem();
#pragma unroll 1
        for (int i = 0; i < NSTAGE; i++) {
            mbar_expect_tx(bar_full + 8 * i, BK * 640);
            tma3d(sbase + i * SLOT, &m_x, i * BK, tok_a * 128, 0, bar_full + 8 * i);
            tma3d(sbase + i * SLOT + BOFF, &m_wqkv, hp * 64, i * BK, 0, bar_full + 8 * i);
        }
    }
    __syncthreads();
    TL(tid == 128, 0);
    TLG(tid == 128, 31);

    if (warp >= 8) {
      asm volatile("setmaxnreg.dec.sync.aligned.u32 120;");
      if (warp == 8) {
        if (lane == 0) {
            uint32_t fb = bar_full, dst = sbase, par = 0;
            auto phase = [&](const CUtensorMap* ma, int a1, int a2, bool a_on_0, const CUtensorMap* mb, int b0, int b2, int k0, uint32_t bytes, int cnt) {
#pragma unroll 1
                for (int i = 0; i < cnt; i++) {
                    mbar_wait<2>(fb + 8 * NSTAGE, par);
                    mbar_expect_tx(fb, bytes);
                    tma3d(dst, ma, a_on_0 ? k0 : 0, a_on_0 ? a1 : k0, a2, fb);
                    tma3d(dst + BOFF, mb, b0, k0, b2, fb);
                    k0 += BK;
                    fb += 8; dst += SLOT;
                    if (fb == bar_full + 8 * NSTAGE) { fb = bar_full; dst = sbase; par ^= 1; }
                }
            };
            auto dep = [&](int flag, unsigned target, int tl) {
                TL(true, tl);
                wait_flag<2>(&g_flags[flag * 32], target, epoch);
                fence_async_glob();
                TL(true, tl + 1);
            };
            phase(&m_x, tok_a * 128, 0, true, &m_wqkv, hp * 64, 0, NSTAGE * BK, BK * 640, 1024 / BK - NSTAGE);
            dep(FL_LN, NCTA, 20);
            phase(&m_h, 0, dt * 2, false, &m_w1, 0, ft * 7, 0, BK * 704, 2048 / BK);
            phase(&m_x, tok_b * 128, 0, true, &m_wqkv, hp * 64, 0, 0, BK * 640, 1024 / BK);
            dep(FL_U + nt, 32, 22);
            phase(&m_w2, 0, st * 2, false, &m_u, 0, nt * 4, kh ? N0 * BK : 0, BK * 768, nB);
            dep(FL_O + st, 16, 24);
            phase(&m_o, 0, st * 2, false, &m_wo, 0, nt * 4, kh ? 512 : 0, BK * 768, 512 / BK);
        }
      } else {
        const int et = tid - 288, sw = warp - 9;
        const int g8 = lane >> 2, t4 = lane & 3;
        {
            for (int idx = et; idx < 256; idx += 96) {
                const int k = (idx >> 2) & 31, u = idx & 3, h = idx >> 7;
                sts128(sbase + OFF_WPHI + h * 4096 + k * 128 + ((u ^ (k & 7)) << 4),
                       __ldg((const uint4*)(prm.wphi + ((size_t)(hp * 2 + h) * 32 + k) * 32 + u * 8)));
            }
#pragma unroll 1
            for (int pr = sw; pr < 4; pr += 3) ln_rows<2>(prm.x, prm.gate_w, cta * 16 + 8 + pr * 2, cta * 16 + 16, lane);
            if (tg == 0 && r == 0) {
#pragma unroll
                for (int i = 0; i < 16; i++) g_kvsum[(hp * 16 + i) * 96 + et] = make_float4(0.f, 0.f, 0.f, 0.f);
            }
            fence_async_glob();
            fence_async_smem();
            bar_sync(1, 96);
            if (et == 0) {
                mbar_arrive(bar_w);
                mbar_wait<1>(bar_ln, 0);
                flag_add(&g_flags[FL_LN * 32]);
            }
        }

#pragma unroll 1
        for (int tile = 0; tile < 2; tile++) {
            if (tile) {
                mbar_wait<1>(bar_stg_full, 1);
#pragma unroll 1
                for (int idx = et; idx < 896; idx += 96) {
                    uint4 a[4];
                    __nv_bfloat162 b[4];
                    const int u = idx & 15;
#pragma unroll
                    for (int h = 0; h < 4; h++) {
                        const int row = (idx >> 4) + h * 56;
                        a[h] = lds128(stg + row * 256 + ((u ^ (row & 7)) << 4));
                        b[h] = __bfloat162bfloat162(__ldg(prm.b1 + ft * 224 + row));
                    }
#pragma unroll
                    for (int h = 0; h < 4; h++) {
                        const int row = (idx >> 4) + h * 56;
                        const uint32_t av[4] = {a[h].x, a[h].y, a[h].z, a[h].w};
                        uint32_t ov[4];
#pragma unroll
                        for (int k = 0; k < 4; k++) {
                            const __nv_bfloat162 ts2 = __hadd2(*(const __nv_bfloat162*)&av[k], b[h]);
                            const uint32_t tsum = *(const uint32_t*)&ts2;
                            ov[k] = h < GH ? av[k] : pack2(gelu_tanh(bf_lo(tsum)), gelu_tanh(bf_hi(tsum)));
                        }
                        *(uint4*)(g_u + (size_t)(ft * 224 + row) * D_ + dt * 128 + u * 8) = make_uint4(ov[0], ov[1], ov[2], ov[3]);
                    }
                }
                fence_async_glob();
                bar_sync(1, 96);
                if (et == 0) {
                    mbar_arrive(bar_stg_empty);
                    flag_add(&g_flags[(FL_U + (dt >> 1)) * 32]);
                }
                TL(et == 0, 13);
            }
            mbar_wait<1>(bar_stg_full, 0);
            for (int idx = et; idx < 256; idx += 96)
                sts128(stg + 32768 + idx * 128 + ((4 ^ (idx & 7)) << 4), make_uint4(0x3F803F80u, 0x3F803F80u, 0x3F803F80u, 0x3F803F80u));
#pragma unroll 1
            for (int it = sw * 2; it < 16; it += (it & 1) ? 5 : 1) {
                const int rb = it >> 1, which = it & 1;
                const uint32_t rowa = stg + (rb * 16 + l7 + lb3 * 8) * 128;
                uint32_t pk[4][4], P[4][4], M[4][4];
#pragma unroll
                for (int j = 0; j < 4; j++)
                    ldsm4(rowa + which * 16384 + (((j * 2 + lb4) ^ l7) << 4), pk[(j >> 1) * 2][(j & 1) * 2], pk[(j >> 1) * 2 + 1][(j & 1) * 2],
                          pk[(j >> 1) * 2][(j & 1) * 2 + 1], pk[(j >> 1) * 2 + 1][(j & 1) * 2 + 1]);
                dual_softmax<4>(pk, P, M);
                if (which == 0) {
                    uint4* dst = &g_pq[(size_t)((cta * 16 + tile * 8 + rb) * 8) * 32 + lane];
#pragma unroll
                    for (int hh = 0; hh < 2; hh++) {
                        dst[(hh * 4 + 0) * 32] = make_uint4(P[2 * hh][0], P[2 * hh + 1][0], P[2 * hh][1], P[2 * hh + 1][1]);
                        dst[(hh * 4 + 1) * 32] = make_uint4(P[2 * hh][2], P[2 * hh + 1][2], P[2 * hh][3], P[2 * hh + 1][3]);
                        dst[(hh * 4 + 2) * 32] = make_uint4(M[2 * hh][0], M[2 * hh + 1][0], M[2 * hh][1], M[2 * hh + 1][1]);
                        dst[(hh * 4 + 3) * 32] = make_uint4(M[2 * hh][2], M[2 * hh + 1][2], M[2 * hh][3], M[2 * hh + 1][3]);
                    }
                } else {
#pragma unroll
                    for (int hh = 0; hh < 2; hh++) {
                        const uint32_t base = rowa + hh * 16384;
                        stmatrix4(base + (((0 + lb4) ^ l7) << 4), P[2 * hh][0], P[2 * hh + 1][0], P[2 * hh][1], P[2 * hh + 1][1]);
                        stmatrix4(base + (((2 + lb4) ^ l7) << 4), P[2 * hh][2], P[2 * hh + 1][2], P[2 * hh][3], P[2 * hh + 1][3]);
                        stmatrix4(base + (((4 + lb4) ^ l7) << 4), M[2 * hh][0], M[2 * hh + 1][0], M[2 * hh][1], M[2 * hh + 1][1]);
                        stmatrix4(base + (((6 + lb4) ^ l7) << 4), M[2 * hh][2], M[2 * hh + 1][2], M[2 * hh][3], M[2 * hh + 1][3]);
                    }
                }
            }
            fence_async_smem();
            if (tile == 0 && et == 0) wait_flag<1>(&g_flags[FL_LN * 32], NCTA, epoch);
            bar_sync(1, 96);
            if (et == 0) mbar_arrive(bar_phi);
            TL(et == 0, tile ? 14 : 12);
        }
        if (et == 0) {
            mbar_wait<1>(bar_kvd, 1);
            flag_add(&g_flags[(FL_KV + hp) * 32]);
            wait_flag<1>(&g_flags[(FL_KV + hp) * 32], 8, epoch);
        }
        bar_sync(1, 96);
        TL(et == 0, 15);
#pragma unroll
        for (int hh = 0; hh < 2; hh++) {
            float4 sv[8];
#pragma unroll
            for (int i = 0; i < 8; i++) sv[i] = __ldcg(&g_kvsum[((hp * 2 + hh) * 8 + i) * 96 + et]);
            const uint32_t base = stg + 32768 + hh * 8192 + (sw * 16 + g8) * 128 + t4 * 4;
#pragma unroll
            for (int i = 0; i < 8; i++) {
                sts32(base + ((i ^ g8) << 4), pack2(sv[i].x, sv[i].y));
                if (sw < 2) sts32(base + 1024 + ((i ^ g8) << 4), pack2(sv[i].z, sv[i].w));
            }
        }
        fence_async_smem();
        bar_sync(1, 96);
        TL(et == 0, 29);
        if (et == 0) {
            mbar_arrive(bar_kvx);
            mbar_wait<1>(bar_od, 0);
            tma3d_store(&m_os, stg, 0, hp * 64, tok_a * 2);
            tma3d_store(&m_os, stg + 16384, 0, hp * 64, tok_b * 2);
            bulk_commit();
            bulk_wait_all();
            fence_async_glob();
            flag_add(&g_flags[(FL_O + tok_a) * 32]);
            asm volatile("red.relaxed.gpu.global.add.u32 [%0], 1;" ::"l"(&g_flags[(FL_O + tok_b) * 32]) : "memory");
            TL(true, 16);
        }
      }
    } else {
        asm volatile("setmaxnreg.inc.sync.aligned.u32 192;");
        const int wg = warp >> 2, wq = warp & 3;
        const int mrow = wg * 64 + wq * 16 + lb3 * 8 + l7;
        Ring ring{0, 0};
        ln_rows<1>(prm.x, prm.gate_w, cta * 16 + warp, cta * 16 + 8, lane);
        fence_async_glob();
        __syncwarp();
        if (lane == 0) mbar_arrive(bar_ln);

        auto kv_section = [&](uint32_t parity) {
            mbar_wait<0>(bar_phi, parity);
            float c[32];
            zero(c);
            pin(c);
            wgmma_fence();
#pragma unroll
            for (int ks = 0; ks < 8; ks++)
                wgmma_n64<1, 1>(c, mkdesc(stg + 32768 + wg * 16384 + ks * 2048, 8192, 1024, 1), mkdesc(stg + wg * 16384 + ks * 2048, 8192, 1024, 1), 1);
            wgmma_commit();
            wgmma_wait<0>();
            pin(c);
            if (wq < 3) {
#pragma unroll
                for (int i = 0; i < 8; i++)
                    red_add4(&g_kvsum[((hp * 2 + wg) * 8 + i) * 96 + wq * 32 + lane],
                             make_float4(c[4 * i], c[4 * i + 1], wq == 2 ? 0.f : c[4 * i + 2], wq == 2 ? 0.f : c[4 * i + 3]));
            }
            __syncwarp();
            if (lane == 0) mbar_arrive(bar_kvd);
        };

#pragma unroll 1
        for (int pass = 0; pass < 2; pass++) {
            {
                float acc[96];
                zero(acc);
                mainloop<0>(acc, 1024 / BK, ring, sbase, bar_full, bar_empty, wg, lane);
                TL(tid == 128, pass ? 5 : 1);
                mbar_wait<0>(pass ? bar_stg_empty : bar_w, 0);
                float pf[4][16];
                {
                    uint32_t a[8][4];
#pragma unroll
                    for (int j = 0; j < 8; j++) {
                        a[j][0] = pack2(acc[8 * j], acc[8 * j + 1]); a[j][1] = pack2(acc[8 * j + 2], acc[8 * j + 3]);
                        a[j][2] = pack2(acc[8 * j + 4], acc[8 * j + 5]); a[j][3] = pack2(acc[8 * j + 6], acc[8 * j + 7]);
                    }
                    zero(pf[0]); zero(pf[1]); zero(pf[2]); zero(pf[3]);
                    pin(pf[0]); pin(pf[1]); pin(pf[2]); pin(pf[3]);
#pragma unroll
                    for (int j = 0; j < 8; j++) { pin(a[j][0]); pin(a[j][1]); pin(a[j][2]); pin(a[j][3]); }
                    wgmma_fence();
#pragma unroll
                    for (int j = 0; j < 8; j++)
                        wgmma_rs_n32<1>(pf[j >> 1], a[j][0], a[j][1], a[j][2], a[j][3], mkdesc(sbase + OFF_WPHI + (j & 3) * 2048, 4096, 1024, 1), 1);
                    wgmma_commit();
                }
                const uint32_t base = stg + mrow * 128;
#pragma unroll
                for (int j = 0; j < 4; j++)
                    stmatrix4(base + 32768 + (j >> 1) * 16384 + ((((j & 1) * 2 + lb4) ^ l7) << 4),
                              pack2(acc[64 + 8 * j], acc[65 + 8 * j]), pack2(acc[66 + 8 * j], acc[67 + 8 * j]),
                              pack2(acc[68 + 8 * j], acc[69 + 8 * j]), pack2(acc[70 + 8 * j], acc[71 + 8 * j]));
                wgmma_wait<0>();
#pragma unroll
                for (int j = 0; j < 8; j++) {
                    const float* f = &pf[j >> 1][(j & 1) * 8];
                    stmatrix4(base + (j >> 2) * 16384 + ((((j & 3) * 2 + lb4) ^ l7) << 4),
                              pack2(f[0], f[1]), pack2(f[2], f[3]), pack2(f[4], f[5]), pack2(f[6], f[7]));
                }
                fence_async_smem();
                __syncwarp();
                if (lane == 0) mbar_arrive(bar_stg_full);
                TL(tid == 128, pass ? 6 : 2);
            }
            if (pass == 0) {
                float acc[112];
                zero(acc);
                mainloop<1>(acc, 2048 / BK, ring, sbase, bar_full, bar_empty, wg, lane);
                TL(tid == 128, 3);
                kv_section(0);
                bar_sync(2, 256);
                const uint32_t base = stg + (lb4 * 8 + l7) * 256 + (((wg * 8 + wq * 2 + lb3) ^ l7) << 4);
                uint32_t pk[56];
#pragma unroll
                for (int i = 0; i < 56; i++) pk[i] = pack2(acc[2 * i], acc[2 * i + 1]);
#pragma unroll
                for (int b = 0; b < 7 * GH; b++) {
                    const __nv_bfloat162 bb = __ldg((const __nv_bfloat162*)(prm.b1 + ft * 224 + b * 8 + (lane & 3) * 2));
#pragma unroll
                    for (int h = 0; h < 2; h++) {
                        const __nv_bfloat162 t2 = __hadd2(*(const __nv_bfloat162*)&pk[2 * b + h], bb);
                        const uint32_t t = *(const uint32_t*)&t2;
                        pk[2 * b + h] = pack2(gelu_tanh(bf_lo(t)), gelu_tanh(bf_hi(t)));
                    }
                }
#pragma unroll
                for (int jb = 0; jb < 14; jb++) stmatrix4t(base + jb * 4096, pk[4 * jb], pk[4 * jb + 1], pk[4 * jb + 2], pk[4 * jb + 3]);
                __syncwarp();
                if (lane == 0) mbar_arrive(bar_stg_full);
                TL(tid == 128, 4);
            }
        }
        float acc[128];
        zero(acc);
        const int grow = st * 128 + wg * 64 + wq * 16 + (lane >> 2);
        mainloop<2>(acc, S1, ring, sbase, bar_full, bar_empty, wg, lane);
        TL(tid == 128, 26);
        kv_section(1);
        TL(tid == 128, 27);
        mainloop<2>(acc, S2 - S1, ring, sbase, bar_full, bar_empty, wg, lane);
        TL(tid == 128, 28);
        {
            const uint4* src = &g_pq[(size_t)((cta * 16 + wg * 8 + wq) * 8) * 32 + lane];
            const int orow = (wg ? tok_b : tok_a) * 128 + wq * 16 + (lane >> 2);
            uint4 qn[4];
#pragma unroll
            for (int i = 0; i < 4; i++) qn[i] = __ldcg(src + i * 32);
            const float ga0 = __ldcg(&g_gate[orow]), ga1 = __ldcg(&g_gate[orow + 8]);
            const float gb0 = __ldcg(&g_gate[orow + 64]), gb1 = __ldcg(&g_gate[orow + 72]);
            mbar_wait<0>(bar_kvx, 0);
#pragma unroll 1
            for (int un = 0; un < 4; un++) {
                const int mb = un >> 1, hh = un & 1;
                uint4 q[4];
#pragma unroll
                for (int i = 0; i < 4; i++) q[i] = qn[i];
                if (un < 3) {
                    const uint4* nsrc = src + (((un + 1) >> 1) * 32 + ((un + 1) & 1) * 4) * 32;
#pragma unroll
                    for (int i = 0; i < 4; i++) qn[i] = __ldcg(nsrc + i * 32);
                }
                const float gt0 = mb ? gb0 : ga0, gt1 = mb ? gb1 : ga1;
                float o[20];
                zero(o);
                pin(o);
#pragma unroll
                for (int i = 0; i < 4; i++) { pin(q[i].x); pin(q[i].y); pin(q[i].z); pin(q[i].w); }
                wgmma_fence();
#pragma unroll
                for (int j = 0; j < 4; j++)
                    wgmma_rs_n40<0>(o, q[j].x, q[j].y, q[j].z, q[j].w, mkdesc(stg + 32768 + hh * 8192 + j * 32, 16, 1024, 1), 1);
                wgmma_commit();
                wgmma_wait<0>();
                pin(o);
#pragma unroll
                for (int i = 0; i < 4; i++) { pin(q[i].x); pin(q[i].y); pin(q[i].z); pin(q[i].w); }
                const float s0 = gt0 * rcp_fast(o[16] + 1e-6f), s1 = gt1 * rcp_fast(o[18] + 1e-6f);
                const uint32_t base = stg + wg * 16384 + mb * 8192 + (hh * 32 + lb4 * 8 + l7) * 128 + (((wq * 2 + lb3) ^ l7) << 4);
                stmatrix4t(base, pack2(o[0] * s0, o[1] * s0), pack2(o[2] * s1, o[3] * s1),
                           pack2(o[4] * s0, o[5] * s0), pack2(o[6] * s1, o[7] * s1));
                stmatrix4t(base + 2048, pack2(o[8] * s0, o[9] * s0), pack2(o[10] * s1, o[11] * s1),
                           pack2(o[12] * s0, o[13] * s0), pack2(o[14] * s1, o[15] * s1));
            }
            fence_async_smem();
            __syncwarp();
            if (lane == 0) mbar_arrive(bar_od);
        }
        TL(tid == 128, 30);
        mainloop<2>(acc, nB - S2, ring, sbase, bar_full, bar_empty, wg, lane);
        TL(tid == 128, 7);
        {
            const float c0 = 1.f - __ldcg(&g_gate[grow]), c1 = 1.f - __ldcg(&g_gate[grow + 8]);
            const float b0 = kh ? __bfloat162float(prm.b2[grow]) : 0.f, b1v = kh ? __bfloat162float(prm.b2[grow + 8]) : 0.f;
#pragma unroll
            for (int i = 0; i < 32; i++) {
                acc[4 * i] = (acc[4 * i] + b0) * c0;
                acc[4 * i + 1] = (acc[4 * i + 1] + b0) * c0;
                acc[4 * i + 2] = (acc[4 * i + 2] + b1v) * c1;
                acc[4 * i + 3] = (acc[4 * i + 3] + b1v) * c1;
            }
        }
        mainloop<2>(acc, 512 / BK, ring, sbase, bar_full, bar_empty, wg, lane);
        TL(tid == 128, 8);
        {
            const int tile = st * 4 + nt;
            uint4* dst = &g_part[(size_t)(tile * 2 + kh) * 8 * 256 + tid];
#pragma unroll
            for (int i = 0; i < 8; i++) {
                uint32_t v[4];
#pragma unroll
                for (int k = 0; k < 4; k++)
                    v[k] = kh ? pack2(acc[8 * i + 2 * k], acc[8 * i + 2 * k + 1]) : pack2(acc[64 + 8 * i + 2 * k], acc[65 + 8 * i + 2 * k]);
                dst[i * 256] = make_uint4(v[0], v[1], v[2], v[3]);
            }
            bar_sync(2, 256);
            if (tid == 0) {
                flag_add(&g_flags[(FL_PART + tile * 2 + kh) * 32]);
                wait_flag<0>(&g_flags[(FL_PART + tile * 2 + (kh ^ 1)) * 32], 1, epoch);
            }
            TL(tid == 128, 17);
            bar_sync(2, 256);
            TL(tid == 128, 10);
            const uint4* src = &g_part[(size_t)(tile * 2 + (kh ^ 1)) * 8 * 256 + tid];
            uint4 pv[8];
#pragma unroll
            for (int i = 0; i < 8; i++) pv[i] = __ldcg(src + i * 256);
            const uint32_t obase = sbase + wg * 16384 + (wq * 16 + lb3 * 8 + l7) * 128;
#pragma unroll
            for (int i = 0; i < 8; i++) {
                float f[8];
#pragma unroll
                for (int k = 0; k < 8; k++) f[k] = kh ? acc[64 + 8 * i + k] : acc[8 * i + k];
                stmatrix4(obase + (i >> 2) * 8192 + (((((2 * i) & 7) + lb4) ^ l7) << 4),
                          pack2(f[0] + bf_lo(pv[i].x), f[1] + bf_hi(pv[i].x)), pack2(f[2] + bf_lo(pv[i].y), f[3] + bf_hi(pv[i].y)),
                          pack2(f[4] + bf_lo(pv[i].z), f[5] + bf_hi(pv[i].z)), pack2(f[6] + bf_lo(pv[i].w), f[7] + bf_hi(pv[i].w)));
            }
            TL(tid == 128, 18);
            fence_async_smem();
            bar_sync(3 + wg, 128);
            TL(tid == 128, 11);
            if ((tid & 127) == 0) {
#pragma unroll
                for (int c = 0; c < 2; c++)
                    tma2d_store(&m_out, sbase + wg * 16384 + c * 8192, nt * 256 + kh * 128 + c * 64, st * 128 + wg * 64);
                bulk_commit();
                bulk_wait_read();
            }
        }
        TL(tid == 128, 9);
        TLG(tid == 128, 19);
    }
}

typedef CUresult (*EncodeFn)(CUtensorMap*, CUtensorMapDataType, cuuint32_t, void*, const cuuint64_t*, const cuuint64_t*,
                             const cuuint32_t*, const cuuint32_t*, CUtensorMapInterleave, CUtensorMapSwizzle,
                             CUtensorMapL2promotion, CUtensorMapFloatOOBfill);

void make_map(EncodeFn enc, CUtensorMap* m, const void* ptr, int rank, const uint64_t* dims, const uint64_t* strides_bytes,
              const uint32_t* box, CUtensorMapSwizzle swz) {
    cuuint64_t gd[3], gs[2];
    cuuint32_t bd[3], es[3] = {1, 1, 1};
    for (int i = 0; i < rank; i++) { gd[i] = dims[i]; bd[i] = box[i]; }
    for (int i = 0; i < rank - 1; i++) gs[i] = strides_bytes[i];
    CUresult res = enc(m, CU_TENSOR_MAP_DATA_TYPE_BFLOAT16, rank, const_cast<void*>(ptr), gd, gs, bd, es, CU_TENSOR_MAP_INTERLEAVE_NONE, swz,
        CU_TENSOR_MAP_L2_PROMOTION_L2_128B, CU_TENSOR_MAP_FLOAT_OOB_FILL_NONE);
    (void)res;
}

}

extern "C" void kernel_launch(void* const* d_in, const int* in_sizes, int n_in, void* d_out, int out_size) {
    (void)in_sizes; (void)n_in; (void)out_size;
    const __nv_bfloat16* x = (const __nv_bfloat16*)d_in[0];
    const __nv_bfloat16* wqkv = (const __nv_bfloat16*)d_in[1];
    const __nv_bfloat16* wphi = (const __nv_bfloat16*)d_in[2];
    const __nv_bfloat16* wo = (const __nv_bfloat16*)d_in[3];
    const __nv_bfloat16* w1 = (const __nv_bfloat16*)d_in[5];
    const __nv_bfloat16* b1 = (const __nv_bfloat16*)d_in[6];
    const __nv_bfloat16* w2 = (const __nv_bfloat16*)d_in[7];
    const __nv_bfloat16* b2 = (const __nv_bfloat16*)d_in[8];
    const __nv_bfloat16* gate_w = (const __nv_bfloat16*)d_in[9];

    EncodeFn enc = nullptr;
    cudaDriverEntryPointQueryResult qr;
    cudaGetDriverEntryPoint("cuTensorMapEncodeTiled", (void**)&enc, cudaEnableDefault, &qr);
    void *p_h, *p_u, *p_o;
    cudaGetSymbolAddress(&p_h, g_h);
    cudaGetSymbolAddress(&p_u, g_u);
    cudaGetSymbolAddress(&p_o, g_o);

    CUtensorMap m_x, m_wqkv, m_h, m_w1, m_w2, m_u, m_o, m_wo, m_os, m_out;
    {
        uint64_t d[3] = {1024, 2048, 1}, s[2] = {2048, 2048 * 2048};
        uint32_t b[3] = {BK, 128, 1};
        make_map(enc, &m_x, x, 3, d, s, b, BK == 64 ? CU_TENSOR_MAP_SWIZZLE_128B : CU_TENSOR_MAP_SWIZZLE_64B);
    }
    {
        uint64_t d[2] = {1024, 2048}, s[1] = {2048};
        uint32_t b[2] = {64, 64};
        make_map(enc, &m_out, d_out, 2, d, s, b, CU_TENSOR_MAP_SWIZZLE_128B);
    }
    {
        uint64_t d[3] = {1024, 1024, 3}, s[2] = {6144, 2048};
        uint32_t b[3] = {64, BK, 3};
        make_map(enc, &m_wqkv, wqkv, 3, d, s, b, CU_TENSOR_MAP_SWIZZLE_128B);
    }
    {
        uint64_t d[3] = {64, 2048, 16}, s[2] = {2048, 128};
        uint32_t b[3] = {64, BK, 2};
        make_map(enc, &m_h, p_h, 3, d, s, b, CU_TENSOR_MAP_SWIZZLE_128B);
    }
    {
        uint64_t d[3] = {32, 2048, 112}, s[2] = {7168, 64};
        uint32_t b[3] = {32, BK, 7};
        make_map(enc, &m_w1, w1, 3, d, s, b, CU_TENSOR_MAP_SWIZZLE_64B);
    }
    {
        uint64_t d[3] = {64, 3584, 32}, s[2] = {4096, 128};
        uint32_t b[3] = {64, BK, 2};
        make_map(enc, &m_w2, w2, 3, d, s, b, CU_TENSOR_MAP_SWIZZLE_128B);
    }
    {
        uint64_t d[3] = {64, 3584, 16}, s[2] = {2048, 128};
        uint32_t b[3] = {64, BK, 4};
        make_map(enc, &m_u, p_u, 3, d, s, b, CU_TENSOR_MAP_SWIZZLE_128B);
    }
    {
        uint64_t d[3] = {64, 1024, 32}, s[2] = {4096, 128};
        uint32_t b[3] = {64, BK, 2};
        make_map(enc, &m_o, p_o, 3, d, s, b, CU_TENSOR_MAP_SWIZZLE_128B);
        uint32_t bs[3] = {64, 64, 2};
        make_map(enc, &m_os, p_o, 3, d, s, bs, CU_TENSOR_MAP_SWIZZLE_128B);
    }
    {
        uint64_t d[3] = {64, 1024, 16}, s[2] = {2048, 128};
        uint32_t b[3] = {64, BK, 4};
        make_map(enc, &m_wo, wo, 3, d, s, b, CU_TENSOR_MAP_SWIZZLE_128B);
    }
    Params prm{x, wphi, b1, b2, gate_w};

    cudaFuncSetAttribute(fused_kernel, cudaFuncAttributeMaxDynamicSharedMemorySize, SMEM_BYTES);
    fused_kernel<<<NCTA, NTHREADS, SMEM_BYTES, cudaStreamPerThread>>>(m_x, m_wqkv, m_h, m_w1, m_w2, m_u, m_o, m_wo, m_os, m_out, prm);
}
```

```cpp
#include <cuda_runtime.h>
#include <cuda.h>
#include <cuda_bf16.h>
#include <stdint.h>

namespace {

constexpr int S_ = 2048, D_ = 1024, F_ = 3584;
constexpr int NCTA = 128;
#define BK_ 32
constexpr int BK = BK_;
constexpr int NSTAGE = 192 / BK;
constexpr int SLOT = BK * 768;
constexpr int BOFF = BK * 256;
constexpr int OFF_STG = NSTAGE * SLOT;
constexpr int OFF_WPHI = OFF_STG + 65536;
constexpr int OFF_BAR = OFF_WPHI + 8192;
constexpr int SMEM_BYTES = OFF_BAR + 256 + 1024;
#define N0_ 28
constexpr int N0 = N0_ * (64 / BK);
constexpr int FB = F_ / BK;
constexpr int NTHREADS = 384;
#define KVA_ 1792
constexpr int KVA = KVA_;
#define GH_ 0
constexpr int GH = GH_;
#define S1_ 14
#define S2_ 20
constexpr int S1 = S1_ * (64 / BK), S2 = S2_ * (64 / BK);

constexpr int FL_LN = 0, FL_U = 1, FL_KV = 5, FL_O = 21, FL_PART = 53, FL_LN1 = 181, FL_LN2 = 182, FL_UF = 183, FL_COUNT = 191;

__device__ __align__(1024) __nv_bfloat16 g_h[S_ * D_];
__device__ __align__(1024) __nv_bfloat16 g_u[F_ * D_];
__device__ __align__(1024) __nv_bfloat16 g_o[D_ * S_];
__device__ __align__(1024) uint4 g_pq[NCTA * 16 * 8 * 32];
__device__ __align__(1024) float4 g_kvsum[16 * 2 * 8 * 96];
__device__ __align__(1024) uint4 g_part[64 * 16 * 256];
__device__ __align__(1024) float g_gate[S_];
__device__ __align__(1024) unsigned g_flags[FL_COUNT * 32];

__device__ __forceinline__ uint32_t smem_u32(const void* p) { return (uint32_t)__cvta_generic_to_shared(p); }
__device__ __forceinline__ void mbar_init(uint32_t bar, uint32_t cnt) {
    asm volatile("mbarrier.init.shared::cta.b64 [%0], %1;" ::"r"(bar), "r"(cnt));
}
__device__ __forceinline__ void mbar_expect_tx(uint32_t bar, uint32_t bytes) {
    asm volatile("mbarrier.arrive.expect_tx.shared::cta.b64 _, [%0], %1;" ::"r"(bar), "r"(bytes) : "memory");
}
__device__ __forceinline__ void mbar_arrive(uint32_t bar) {
    asm volatile("mbarrier.arrive.shared::cta.b64 _, [%0];" ::"r"(bar) : "memory");
}
template <int ROLE>
__device__ __forceinline__ void mbar_wait(uint32_t bar, uint32_t parity) {
    uint32_t done;
    int n = 0;
    while (true) {
        asm volatile("{\n.reg .pred p;\nmbarrier.try_wait.parity.shared::cta.b64 p, [%1], %2;\nselp.u32 %0, 1, 0, p;\n}"
                     : "=r"(done) : "r"(bar), "r"(parity) : "memory");
        if (done || ++n >= (1 << 22)) break;
    }
}
__device__ __forceinline__ unsigned ld_relaxed(const unsigned* p) {
    unsigned v;
    asm volatile("ld.relaxed.gpu.global.u32 %0, [%1];" : "=r"(v) : "l"(p) : "memory");
    return v;
}
template <int ROLE>
__device__ __forceinline__ void wait_flag(const unsigned* p, unsigned target, unsigned epoch) {
    unsigned v;
    int n = 0;
    const unsigned base = epoch * target;
    while (true) {
        asm volatile("ld.acquire.gpu.global.u32 %0, [%1];" : "=r"(v) : "l"(p) : "memory");
        if (v - base >= target) break;
        if (++n > (1 << 20)) break;
        __nanosleep(40);
    }
}
__device__ __forceinline__ void flag_add(unsigned* p) {
    asm volatile("red.release.gpu.global.add.u32 [%0], 1;" ::"l"(p) : "memory");
}
__device__ __forceinline__ void fence_async_smem() { asm volatile("fence.proxy.async.shared::cta;" ::: "memory"); }
__device__ __forceinline__ void fence_async_glob() { asm volatile("fence.proxy.async.global;" ::: "memory"); }
__device__ __forceinline__ void bar_sync(int id, int n) {
    __syncwarp();
    asm volatile("bar.sync %0, %1;" ::"r"(id), "r"(n) : "memory");
}

__device__ __forceinline__ void tma3d(uint32_t dst, const CUtensorMap* m, int c0, int c1, int c2, uint32_t bar) {
    asm volatile("cp.async.bulk.tensor.3d.shared::cluster.global.mbarrier::complete_tx::bytes [%0], [%1, {%3, %4, %5}], [%2];"
                 ::"r"(dst), "l"((uint64_t)m), "r"(bar), "r"(c0), "r"(c1), "r"(c2) : "memory");
}
__device__ __forceinline__ void tma2d_store(const CUtensorMap* m, uint32_t src, int c0, int c1) {
    asm volatile("cp.async.bulk.tensor.2d.global.shared::cta.bulk_group [%0, {%2, %3}], [%1];"
                 ::"l"((uint64_t)m), "r"(src), "r"(c0), "r"(c1) : "memory");
}
__device__ __forceinline__ void tma3d_store(const CUtensorMap* m, uint32_t src, int c0, int c1, int c2) {
    asm volatile("cp.async.bulk.tensor.3d.global.shared::cta.bulk_group [%0, {%2, %3, %4}], [%1];"
                 ::"l"((uint64_t)m), "r"(src), "r"(c0), "r"(c1), "r"(c2) : "memory");
}
__device__ __forceinline__ void bulk_commit() { asm volatile("cp.async.bulk.commit_group;" ::: "memory"); }
__device__ __forceinline__ void bulk_wait_all() { asm volatile("cp.async.bulk.wait_group 0;" ::: "memory"); }
__device__ __forceinline__ void bulk_wait_read() { asm volatile("cp.async.bulk.wait_group.read 0;" ::: "memory"); }

__device__ __forceinline__ void wgmma_fence() { asm volatile("wgmma.fence.sync.aligned;" ::: "memory"); }
__device__ __forceinline__ void wgmma_commit() { asm volatile("wgmma.commit_group.sync.aligned;" ::: "memory"); }
template <int N>
__device__ __forceinline__ void wgmma_wait() { asm volatile("wgmma.wait_group.sync.aligned %0;" ::"n"(N) : "memory"); }

__device__ __forceinline__ uint64_t mkdesc(uint32_t addr, uint32_t lbo, uint32_t sbo, uint32_t swz) {
    return (uint64_t)((addr & 0x3FFFF) >> 4) | ((uint64_t)(lbo >> 4) << 16) | ((uint64_t)(sbo >> 4) << 32) | ((uint64_t)swz << 62);
}
__device__ __forceinline__ uint32_t pack2(float lo, float hi) {
    uint32_t r;
    asm("cvt.rn.bf16x2.f32 %0, %1, %2;" : "=r"(r) : "f"(hi), "f"(lo));
    return r;
}
__device__ __forceinline__ float bf_lo(uint32_t v) { return __uint_as_float(v << 16); }
__device__ __forceinline__ float bf_hi(uint32_t v) { return __uint_as_float(v & 0xFFFF0000u); }
__device__ __forceinline__ void stmatrix4(uint32_t addr, uint32_t r0, uint32_t r1, uint32_t r2, uint32_t r3) {
    asm volatile("stmatrix.sync.aligned.m8n8.x4.shared.b16 [%0], {%1, %2, %3, %4};" ::"r"(addr), "r"(r0), "r"(r1), "r"(r2), "r"(r3) : "memory");
}
__device__ __forceinline__ void stmatrix4t(uint32_t addr, uint32_t r0, uint32_t r1, uint32_t r2, uint32_t r3) {
    asm volatile("stmatrix.sync.aligned.m8n8.x4.trans.shared.b16 [%0], {%1, %2, %3, %4};" ::"r"(addr), "r"(r0), "r"(r1), "r"(r2), "r"(r3) : "memory");
}
__device__ __forceinline__ void ldsm4(uint32_t addr, uint32_t& r0, uint32_t& r1, uint32_t& r2, uint32_t& r3) {
    asm volatile("ldmatrix.sync.aligned.m8n8.x4.shared.b16 {%0, %1, %2, %3}, [%4];" : "=r"(r0), "=r"(r1), "=r"(r2), "=r"(r3) : "r"(addr) : "memory");
}
__device__ __forceinline__ uint4 lds128(uint32_t addr) {
    uint4 v;
    asm volatile("ld.shared.v4.u32 {%0, %1, %2, %3}, [%4];" : "=r"(v.x), "=r"(v.y), "=r"(v.z), "=r"(v.w) : "r"(addr) : "memory");
    return v;
}
__device__ __forceinline__ void sts128(uint32_t addr, uint4 v) {
    asm volatile("st.shared.v4.u32 [%0], {%1, %2, %3, %4};" ::"r"(addr), "r"(v.x), "r"(v.y), "r"(v.z), "r"(v.w) : "memory");
}
__device__ __forceinline__ void sts32(uint32_t addr, uint32_t v) {
    asm volatile("st.shared.u32 [%0], %1;" ::"r"(addr), "r"(v) : "memory");
}
__device__ __forceinline__ float ex2(float x) {
    float r;
    asm("ex2.approx.ftz.f32 %0, %1;" : "=f"(r) : "f"(x));
    return r;
}
__device__ __forceinline__ float rcp_fast(float x) {
    float r;
    asm("rcp.approx.ftz.f32 %0, %1;" : "=f"(r) : "f"(x));
    return r;
}
__device__ __forceinline__ void red_add4(float4* p, float4 v) {
    asm volatile("red.relaxed.gpu.global.add.v4.f32 [%0], {%1, %2, %3, %4};" ::"l"(p), "f"(v.x), "f"(v.y), "f"(v.z), "f"(v.w) : "memory");
}
__device__ __forceinline__ float tanh_fast(float x) {
    float r;
    asm("tanh.approx.f32 %0, %1;" : "=f"(r) : "f"(x));
    return r;
}
__device__ __forceinline__ float gelu_tanh(float u) {
    const float z = u * fmaf(u * u, 0.7978845608028654f * 0.044715f, 0.7978845608028654f);
    const float hu = 0.5f * u;
    return fmaf(hu, tanh_fast(z), hu);
}

template <int N>
__device__ __forceinline__ void zero(float (&a)[N]) {
#pragma unroll
    for (int i = 0; i < N; i++) a[i] = 0.f;
}

template <int N>
__device__ __forceinline__ void pin(float (&a)[N]) {
#pragma unroll
    for (int i = 0; i < N; i++) asm volatile("" : "+f"(a[i])::"memory");
}
__device__ __forceinline__ void pin(uint32_t& a) { asm volatile("" : "+r"(a)::"memory"); }

template <int TA, int TB>
__device__ __forceinline__ void wgmma_n192(float (&d)[96], uint64_t da, uint64_t db, int scale_d) {
    asm volatile("{\n.reg .pred p;\nsetp.ne.b32 p, %98, 0;\n"
        "wgmma.mma_async.sync.aligned.m64n192k16.f32.bf16.bf16 {%0, %1, %2, %3, %4, %5, %6, %7, %8, %9, %10, %11, %12, %13, %14, %15, %16, %17, %18, %19, %20, %21, %22, %23, %24, %25, %26, %27, %28, %29, %30, %31, %32, %33, %34, %35, %36, %37, %38, %39, %40, %41, %42, %43, %44, %45, %46, %47, %48, %49, %50, %51, %52, %53, %54, %55, %56, %57, %58, %59, %60, %61, %62, %63, %64, %65, %66, %67, %68, %69, %70, %71, %72, %73, %74, %75, %76, %77, %78, %79, %80, %81, %82, %83, %84, %85, %86, %87, %88, %89, %90, %91, %92, %93, %94, %95}, %96, %97, p, 1, 1, %99, %100;\n}\n"
        : "+f"(d[0]), "+f"(d[1]), "+f"(d[2]), "+f"(d[3]), "+f"(d[4]), "+f"(d[5]), "+f"(d[6]), "+f"(d[7]), "+f"(d[8]), "+f"(d[9]), "+f"(d[10]), "+f"(d[11]), "+f"(d[12]), "+f"(d[13]), "+f"(d[14]), "+f"(d[15]), "+f"(d[16]), "+f"(d[17]), "+f"(d[18]), "+f"(d[19]), "+f"(d[20]), "+f"(d[21]), "+f"(d[22]), "+f"(d[23]), "+f"(d[24]), "+f"(d[25]), "+f"(d[26]), "+f"(d[27]), "+f"(d[28]), "+f"(d[29]), "+f"(d[30]), "+f"(d[31]), "+f"(d[32]), "+f"(d[33]), "+f"(d[34]), "+f"(d[35]), "+f"(d[36]), "+f"(d[37]), "+f"(d[38]), "+f"(d[39]), "+f"(d[40]), "+f"(d[41]), "+f"(d[42]), "+f"(d[43]), "+f"(d[44]), "+f"(d[45]), "+f"(d[46]), "+f"(d[47]), "+f"(d[48]), "+f"(d[49]), "+f"(d[50]), "+f"(d[51]), "+f"(d[52]), "+f"(d[53]), "+f"(d[54]), "+f"(d[55]), "+f"(d[56]), "+f"(d[57]), "+f"(d[58]), "+f"(d[59]), "+f"(d[60]), "+f"(d[61]), "+f"(d[62]), "+f"(d[63]), "+f"(d[64]), "+f"(d[65]), "+f"(d[66]), "+f"(d[67]), "+f"(d[68]), "+f"(d[69]), "+f"(d[70]), "+f"(d[71]), "+f"(d[72]), "+f"(d[73]), "+f"(d[74]), "+f"(d[75]), "+f"(d[76]), "+f"(d[77]), "+f"(d[78]), "+f"(d[79]), "+f"(d[80]), "+f"(d[81]), "+f"(d[82]), "+f"(d[83]), "+f"(d[84]), "+f"(d[85]), "+f"(d[86]), "+f"(d[87]), "+f"(d[88]), "+f"(d[89]), "+f"(d[90]), "+f"(d[91]), "+f"(d[92]), "+f"(d[93]), "+f"(d[94]), "+f"(d[95])
        : "l"(da), "l"(db), "r"(scale_d), "n"(TA), "n"(TB));
}
template <int TA, int TB>
__device__ __forceinline__ void wgmma_n224(float (&d)[112], uint64_t da, uint64_t db, int scale_d) {
    asm volatile("{\n.reg .pred p;\nsetp.ne.b32 p, %114, 0;\n"
        "wgmma.mma_async.sync.aligned.m64n224k16.f32.bf16.bf16 {%0, %1, %2, %3, %4, %5, %6, %7, %8, %9, %10, %11, %12, %13, %14, %15, %16, %17, %18, %19, %20, %21, %22, %23, %24, %25, %26, %27, %28, %29, %30, %31, %32, %33, %34, %35, %36, %37, %38, %39, %40, %41, %42, %43, %44, %45, %46, %47, %48, %49, %50, %51, %52, %53, %54, %55, %56, %57, %58, %59, %60, %61, %62, %63, %64, %65, %66, %67, %68, %69, %70, %71, %72, %73, %74, %75, %76, %77, %78, %79, %80, %81, %82, %83, %84, %85, %86, %87, %88, %89, %90, %91, %92, %93, %94, %95, %96, %97, %98, %99, %100, %101, %102, %103, %104, %105, %106, %107, %108, %109, %110, %111}, %112, %113, p, 1, 1, %115, %116;\n}\n"
        : "+f"(d[0]), "+f"(d[1]), "+f"(d[2]), "+f"(d[3]), "+f"(d[4]), "+f"(d[5]), "+f"(d[6]), "+f"(d[7]), "+f"(d[8]), "+f"(d[9]), "+f"(d[10]), "+f"(d[11]), "+f"(d[12]), "+f"(d[13]), "+f"(d[14]), "+f"(d[15]), "+f"(d[16]), "+f"(d[17]), "+f"(d[18]), "+f"(d[19]), "+f"(d[20]), "+f"(d[21]), "+f"(d[22]), "+f"(d[23]), "+f"(d[24]), "+f"(d[25]), "+f"(d[26]), "+f"(d[27]), "+f"(d[28]), "+f"(d[29]), "+f"(d[30]), "+f"(d[31]), "+f"(d[32]), "+f"(d[33]), "+f"(d[34]), "+f"(d[35]), "+f"(d[36]), "+f"(d[37]), "+f"(d[38]), "+f"(d[39]), "+f"(d[40]), "+f"(d[41]), "+f"(d[42]), "+f"(d[43]), "+f"(d[44]), "+f"(d[45]), "+f"(d[46]), "+f"(d[47]), "+f"(d[48]), "+f"(d[49]), "+f"(d[50]), "+f"(d[51]), "+f"(d[52]), "+f"(d[53]), "+f"(d[54]), "+f"(d[55]), "+f"(d[56]), "+f"(d[57]), "+f"(d[58]), "+f"(d[59]), "+f"(d[60]), "+f"(d[61]), "+f"(d[62]), "+f"(d[63]), "+f"(d[64]), "+f"(d[65]), "+f"(d[66]), "+f"(d[67]), "+f"(d[68]), "+f"(d[69]), "+f"(d[70]), "+f"(d[71]), "+f"(d[72]), "+f"(d[73]), "+f"(d[74]), "+f"(d[75]), "+f"(d[76]), "+f"(d[77]), "+f"(d[78]), "+f"(d[79]), "+f"(d[80]), "+f"(d[81]), "+f"(d[82]), "+f"(d[83]), "+f"(d[84]), "+f"(d[85]), "+f"(d[86]), "+f"(d[87]), "+f"(d[88]), "+f"(d[89]), "+f"(d[90]), "+f"(d[91]), "+f"(d[92]), "+f"(d[93]), "+f"(d[94]), "+f"(d[95]), "+f"(d[96]), "+f"(d[97]), "+f"(d[98]), "+f"(d[99]), "+f"(d[100]), "+f"(d[101]), "+f"(d[102]), "+f"(d[103]), "+f"(d[104]), "+f"(d[105]), "+f"(d[106]), "+f"(d[107]), "+f"(d[108]), "+f"(d[109]), "+f"(d[110]), "+f"(d[111])
        : "l"(da), "l"(db), "r"(scale_d), "n"(TA), "n"(TB));
}
template <int TA, int TB>
__device__ __forceinline__ void wgmma_n256(float (&d)[128], uint64_t da, uint64_t db, int scale_d) {
    asm volatile("{\n.reg .pred p;\nsetp.ne.b32 p, %130, 0;\n"
        "wgmma.mma_async.sync.aligned.m64n256k16.f32.bf16.bf16 {%0, %1, %2, %3, %4, %5, %6, %7, %8, %9, %10, %11, %12, %13, %14, %15, %16, %17, %18, %19, %20, %21, %22, %23, %24, %25, %26, %27, %28, %29, %30, %31, %32, %33, %34, %35, %36, %37, %38, %39, %40, %41, %42, %43, %44, %45, %46, %47, %48, %49, %50, %51, %52, %53, %54, %55, %56, %57, %58, %59, %60, %61, %62, %63, %64, %65, %66, %67, %68, %69, %70, %71, %72, %73, %74, %75, %76, %77, %78, %79, %80, %81, %82, %83, %84, %85, %86, %87, %88, %89, %90, %91, %92, %93, %94, %95, %96, %97, %98, %99, %100, %101, %102, %103, %104, %105, %106, %107, %108, %109, %110, %111, %112, %113, %114, %115, %116, %117, %118, %119, %120, %121, %122, %123, %124, %125, %126, %127}, %128, %129, p, 1, 1, %131, %132;\n}\n"
        : "+f"(d[0]), "+f"(d[1]), "+f"(d[2]), "+f"(d[3]), "+f"(d[4]), "+f"(d[5]), "+f"(d[6]), "+f"(d[7]), "+f"(d[8]), "+f"(d[9]), "+f"(d[10]), "+f"(d[11]), "+f"(d[12]), "+f"(d[13]), "+f"(d[14]), "+f"(d[15]), "+f"(d[16]), "+f"(d[17]), "+f"(d[18]), "+f"(d[19]), "+f"(d[20]), "+f"(d[21]), "+f"(d[22]), "+f"(d[23]), "+f"(d[24]), "+f"(d[25]), "+f"(d[26]), "+f"(d[27]), "+f"(d[28]), "+f"(d[29]), "+f"(d[30]), "+f"(d[31]), "+f"(d[32]), "+f"(d[33]), "+f"(d[34]), "+f"(d[35]), "+f"(d[36]), "+f"(d[37]), "+f"(d[38]), "+f"(d[39]), "+f"(d[40]), "+f"(d[41]), "+f"(d[42]), "+f"(d[43]), "+f"(d[44]), "+f"(d[45]), "+f"(d[46]), "+f"(d[47]), "+f"(d[48]), "+f"(d[49]), "+f"(d[50]), "+f"(d[51]), "+f"(d[52]), "+f"(d[53]), "+f"(d[54]), "+f"(d[55]), "+f"(d[56]), "+f"(d[57]), "+f"(d[58]), "+f"(d[59]), "+f"(d[60]), "+f"(d[61]), "+f"(d[62]), "+f"(d[63]), "+f"(d[64]), "+f"(d[65]), "+f"(d[66]), "+f"(d[67]), "+f"(d[68]), "+f"(d[69]), "+f"(d[70]), "+f"(d[71]), "+f"(d[72]), "+f"(d[73]), "+f"(d[74]), "+f"(d[75]), "+f"(d[76]), "+f"(d[77]), "+f"(d[78]), "+f"(d[79]), "+f"(d[80]), "+f"(d[81]), "+f"(d[82]), "+f"(d[83]), "+f"(d[84]), "+f"(d[85]), "+f"(d[86]), "+f"(d[87]), "+f"(d[88]), "+f"(d[89]), "+f"(d[90]), "+f"(d[91]), "+f"(d[92]), "+f"(d[93]), "+f"(d[94]), "+f"(d[95]), "+f"(d[96]), "+f"(d[97]), "+f"(d[98]), "+f"(d[99]), "+f"(d[100]), "+f"(d[101]), "+f"(d[102]), "+f"(d[103]), "+f"(d[104]), "+f"(d[105]), "+f"(d[106]), "+f"(d[107]), "+f"(d[108]), "+f"(d[109]), "+f"(d[110]), "+f"(d[111]), "+f"(d[112]), "+f"(d[113]), "+f"(d[114]), "+f"(d[115]), "+f"(d[116]), "+f"(d[117]), "+f"(d[118]), "+f"(d[119]), "+f"(d[120]), "+f"(d[121]), "+f"(d[122]), "+f"(d[123]), "+f"(d[124]), "+f"(d[125]), "+f"(d[126]), "+f"(d[127])
        : "l"(da), "l"(db), "r"(scale_d), "n"(TA), "n"(TB));
}
template <int TA, int TB>
__device__ __forceinline__ void wgmma_n64(float (&d)[32], uint64_t da, uint64_t db, int scale_d) {
    asm volatile("{\n.reg .pred p;\nsetp.ne.b32 p, %34, 0;\n"
        "wgmma.mma_async.sync.aligned.m64n64k16.f32.bf16.bf16 {%0, %1, %2, %3, %4, %5, %6, %7, %8, %9, %10, %11, %12, %13, %14, %15, %16, %17, %18, %19, %20, %21, %22, %23, %24, %25, %26, %27, %28, %29, %30, %31}, %32, %33, p, 1, 1, %35, %36;\n}\n"
        : "+f"(d[0]), "+f"(d[1]), "+f"(d[2]), "+f"(d[3]), "+f"(d[4]), "+f"(d[5]), "+f"(d[6]), "+f"(d[7]), "+f"(d[8]), "+f"(d[9]), "+f"(d[10]), "+f"(d[11]), "+f"(d[12]), "+f"(d[13]), "+f"(d[14]), "+f"(d[15]), "+f"(d[16]), "+f"(d[17]), "+f"(d[18]), "+f"(d[19]), "+f"(d[20]), "+f"(d[21]), "+f"(d[22]), "+f"(d[23]), "+f"(d[24]), "+f"(d[25]), "+f"(d[26]), "+f"(d[27]), "+f"(d[28]), "+f"(d[29]), "+f"(d[30]), "+f"(d[31])
        : "l"(da), "l"(db), "r"(scale_d), "n"(TA), "n"(TB));
}
template <int TB>
__device__ __forceinline__ void wgmma_rs_n32(float (&d)[16], uint32_t a0, uint32_t a1, uint32_t a2, uint32_t a3, uint64_t db, int scale_d) {
    asm volatile("{\n.reg .pred p;\nsetp.ne.b32 p, %21, 0;\n"
        "wgmma.mma_async.sync.aligned.m64n32k16.f32.bf16.bf16 {%0, %1, %2, %3, %4, %5, %6, %7, %8, %9, %10, %11, %12, %13, %14, %15}, {%16, %17, %18, %19}, %20, p, 1, 1, %22;\n}\n"
        : "+f"(d[0]), "+f"(d[1]), "+f"(d[2]), "+f"(d[3]), "+f"(d[4]), "+f"(d[5]), "+f"(d[6]), "+f"(d[7]), "+f"(d[8]), "+f"(d[9]), "+f"(d[10]), "+f"(d[11]), "+f"(d[12]), "+f"(d[13]), "+f"(d[14]), "+f"(d[15])
        : "r"(a0), "r"(a1), "r"(a2), "r"(a3), "l"(db), "r"(scale_d), "n"(TB));
}
template <int TB>
__device__ __forceinline__ void wgmma_rs_n40(float (&d)[20], uint32_t a0, uint32_t a1, uint32_t a2, uint32_t a3, uint64_t db, int scale_d) {
    asm volatile("{\n.reg .pred p;\nsetp.ne.b32 p, %25, 0;\n"
        "wgmma.mma_async.sync.aligned.m64n40k16.f32.bf16.bf16 {%0, %1, %2, %3, %4, %5, %6, %7, %8, %9, %10, %11, %12, %13, %14, %15, %16, %17, %18, %19}, {%20, %21, %22, %23}, %24, p, 1, 1, %26;\n}\n"
        : "+f"(d[0]), "+f"(d[1]), "+f"(d[2]), "+f"(d[3]), "+f"(d[4]), "+f"(d[5]), "+f"(d[6]), "+f"(d[7]), "+f"(d[8]), "+f"(d[9]), "+f"(d[10]), "+f"(d[11]), "+f"(d[12]), "+f"(d[13]), "+f"(d[14]), "+f"(d[15]), "+f"(d[16]), "+f"(d[17]), "+f"(d[18]), "+f"(d[19])
        : "r"(a0), "r"(a1), "r"(a2), "r"(a3), "l"(db), "r"(scale_d), "n"(TB));
}

struct Ring {
    uint32_t s, ph;
    __device__ __forceinline__ void next() {
        if (++s == NSTAGE) { s = 0; ph ^= 1; }
    }
};

template <int MODE, int NACC>
__device__ __forceinline__ void mainloop(float (&acc)[NACC], int nkb, Ring& ring, uint32_t sbase, uint32_t bar_full,
                                         uint32_t bar_empty, int wg, int lane) {
    uint32_t prev_s = 0;
#pragma unroll 1
    for (int kb = 0; kb < nkb; kb++) {
        const uint32_t slot = sbase + ring.s * SLOT;
        mbar_wait<0>(bar_full + 8 * ring.s, ring.ph);
        wgmma_fence();
#pragma unroll
        for (int j = 0; j < BK / 16; j++) {
            if constexpr (MODE == 0) {
                wgmma_n192<0, 1>(acc, mkdesc(slot + wg * (BK * 128) + j * 32, 16, BK * 16, BK == 64 ? 1 : 2), mkdesc(slot + BOFF + j * 2048, BK * 128, 1024, 1), 1);
            } else if constexpr (MODE == 1) {
                wgmma_n224<1, 1>(acc, mkdesc(slot + wg * (BK * 128) + j * 2048, BK * 128, 1024, 1), mkdesc(slot + BOFF + j * 1024, BK * 64, 512, 2), 1);
            } else {
                wgmma_n256<1, 1>(acc, mkdesc(slot + wg * (BK * 128) + j * 2048, BK * 128, 1024, 1), mkdesc(slot + BOFF + j * 2048, BK * 128, 1024, 1), 1);
            }
        }
        wgmma_commit();
        if (kb > 0) {
            wgmma_wait<1>();
            if (lane == 0) mbar_arrive(bar_empty + 8 * prev_s);
        }
        prev_s = ring.s;
        ring.next();
    }
    wgmma_wait<0>();
    if (lane == 0) mbar_arrive(bar_empty + 8 * prev_s);
}

template <int NC>
__device__ __forceinline__ void dual_softmax(const uint32_t (&pk)[NC][4], uint32_t (&P)[NC][4], uint32_t (&M)[NC][4]) {
    constexpr float L2E = 1.4426950408889634f;
    uint32_t mm[NC];
#pragma unroll
    for (int c = 0; c < NC; c++) {
        __nv_bfloat162 a0 = *(const __nv_bfloat162*)&pk[c][0], a1 = *(const __nv_bfloat162*)&pk[c][1];
        __nv_bfloat162 a2 = *(const __nv_bfloat162*)&pk[c][2], a3 = *(const __nv_bfloat162*)&pk[c][3];
        __nv_bfloat162 mx = __hmax2(__hmax2(a0, a1), __hmax2(a2, a3));
        __nv_bfloat162 mn = __hmin2(__hmin2(a0, a1), __hmin2(a2, a3));
        const uint32_t umx = *(const uint32_t*)&mx, umn = (*(const uint32_t*)&mn) ^ 0x80008000u;
        const uint32_t lo = __byte_perm(umx, umn, 0x5410), hi = __byte_perm(umx, umn, 0x7632);
        __nv_bfloat162 r = __hmax2(*(const __nv_bfloat162*)&lo, *(const __nv_bfloat162*)&hi);
        mm[c] = *(const uint32_t*)&r;
    }
#pragma unroll
    for (int o = 1; o <= 2; o <<= 1) {
        uint32_t t[NC];
#pragma unroll
        for (int c = 0; c < NC; c++) t[c] = __shfl_xor_sync(0xffffffffu, mm[c], o);
#pragma unroll
        for (int c = 0; c < NC; c++) {
            __nv_bfloat162 r = __hmax2(*(const __nv_bfloat162*)&mm[c], *(const __nv_bfloat162*)&t[c]);
            mm[c] = *(const uint32_t*)&r;
        }
    }
    float ep[NC][8], em[NC][8], sp[NC], sm[NC];
#pragma unroll
    for (int c = 0; c < NC; c++) {
        const float mxs = bf_lo(mm[c]) * L2E, mns = bf_hi(mm[c]) * L2E;
#pragma unroll
        for (int i = 0; i < 4; i++) {
            const float a = bf_lo(pk[c][i]), b = bf_hi(pk[c][i]);
            ep[c][2 * i] = ex2(fmaf(a, L2E, -mxs));
            ep[c][2 * i + 1] = ex2(fmaf(b, L2E, -mxs));
            em[c][2 * i] = ex2(fmaf(a, -L2E, -mns));
            em[c][2 * i + 1] = ex2(fmaf(b, -L2E, -mns));
        }
        sp[c] = ((ep[c][0] + ep[c][1]) + (ep[c][2] + ep[c][3])) + ((ep[c][4] + ep[c][5]) + (ep[c][6] + ep[c][7]));
        sm[c] = ((em[c][0] + em[c][1]) + (em[c][2] + em[c][3])) + ((em[c][4] + em[c][5]) + (em[c][6] + em[c][7]));
    }
#pragma unroll
    for (int o = 1; o <= 2; o <<= 1) {
        float tp[NC], tm[NC];
#pragma unroll
        for (int c = 0; c < NC; c++) {
            tp[c] = __shfl_xor_sync(0xffffffffu, sp[c], o);
            tm[c] = __shfl_xor_sync(0xffffffffu, sm[c], o);
        }
#pragma unroll
        for (int c = 0; c < NC; c++) { sp[c] += tp[c]; sm[c] += tm[c]; }
    }
#pragma unroll
    for (int c = 0; c < NC; c++) {
        const float rp = rcp_fast(sp[c]), rm = rcp_fast(sm[c]);
#pragma unroll
        for (int i = 0; i < 4; i++) {
            P[c][i] = pack2(ep[c][2 * i] * rp, ep[c][2 * i + 1] * rp);
            M[c][i] = pack2(em[c][2 * i] * rm, em[c][2 * i + 1] * rm);
        }
    }
}

template <int NR>
__device__ __forceinline__ void ln_rows(const __nv_bfloat16* x, const __nv_bfloat16* gate_w, int row0, int row_end, int lane) {
    uint4 v[NR][4];
    float sh[NR], red[NR][3];
#pragma unroll
    for (int h = 0; h < NR; h++) {
        const int row = min(row0 + h, row_end - 1);
#pragma unroll
        for (int c = 0; c < 4; c++) v[h][c] = __ldg((const uint4*)(x + (size_t)row * D_) + c * 32 + lane);
        sh[h] = __bfloat162float(__ldg(x + (size_t)row * D_));
        red[h][0] = red[h][1] = red[h][2] = 0.f;
    }
#pragma unroll
    for (int c = 0; c < 4; c++) {
        const uint4 gw = __ldg((const uint4*)gate_w + c * 32 + lane);
        const uint32_t q[4] = {gw.x, gw.y, gw.z, gw.w};
#pragma unroll
        for (int h = 0; h < NR; h++) {
            const uint32_t w[4] = {v[h][c].x, v[h][c].y, v[h][c].z, v[h][c].w};
            float s0 = 0.f, q0 = 0.f, d0 = 0.f;
#pragma unroll
            for (int k = 0; k < 4; k++) {
                const float a = bf_lo(w[k]) - sh[h], b = bf_hi(w[k]) - sh[h];
                s0 += a + b;
                q0 = fmaf(a, a, fmaf(b, b, q0));
                d0 = fmaf(bf_lo(w[k]), bf_lo(q[k]), fmaf(bf_hi(w[k]), bf_hi(q[k]), d0));
            }
            red[h][0] += s0; red[h][1] += q0; red[h][2] += d0;
        }
    }
#pragma unroll
    for (int o = 16; o > 0; o >>= 1) {
        float t[NR][3];
#pragma unroll
        for (int h = 0; h < NR; h++)
#pragma unroll
            for (int k = 0; k < 3; k++) t[h][k] = __shfl_xor_sync(0xffffffffu, red[h][k], o);
#pragma unroll
        for (int h = 0; h < NR; h++)
#pragma unroll
            for (int k = 0; k < 3; k++) red[h][k] += t[h][k];
    }
#pragma unroll
    for (int h = 0; h < NR; h++) {
        if (row0 + h < row_end) {
            const float ms = red[h][0] * (1.f / D_);
            const float var = fmaxf(red[h][1] * (1.f / D_) - ms * ms, 0.f);
            const float rstd = rsqrtf(var + 1e-5f);
            const float nm = -(ms + sh[h]) * rstd;
            uint4* hr = (uint4*)(g_h + (size_t)(row0 + h) * D_) + lane;
#pragma unroll
            for (int c = 0; c < 4; c++) {
                uint4 o;
                o.x = pack2(fmaf(bf_lo(v[h][c].x), rstd, nm), fmaf(bf_hi(v[h][c].x), rstd, nm));
                o.y = pack2(fmaf(bf_lo(v[h][c].y), rstd, nm), fmaf(bf_hi(v[h][c].y), rstd, nm));
                o.z = pack2(fmaf(bf_lo(v[h][c].z), rstd, nm), fmaf(bf_hi(v[h][c].z), rstd, nm));
                o.w = pack2(fmaf(bf_lo(v[h][c].w), rstd, nm), fmaf(bf_hi(v[h][c].w), rstd, nm));
                hr[c * 32] = o;
            }
            if (lane == 0) g_gate[row0 + h] = 1.f / (1.f + __expf(-red[h][2]));
        }
    }
}

struct Params {
    const __nv_bfloat16* x;
    const __nv_bfloat16* wphi;
    const __nv_bfloat16* b1;
    const __nv_bfloat16* b2;
    const __nv_bfloat16* gate_w;
};

__global__ void __launch_bounds__(NTHREADS, 1)
fused_kernel(const __grid_constant__ CUtensorMap m_x, const __grid_constant__ CUtensorMap m_wqkv,
             const __grid_constant__ CUtensorMap m_h, const __grid_constant__ CUtensorMap m_w1,
             const __grid_constant__ CUtensorMap m_w2, const __grid_constant__ CUtensorMap m_u,
             const __grid_constant__ CUtensorMap m_o, const __grid_constant__ CUtensorMap m_wo,
             const __grid_constant__ CUtensorMap m_os, const __grid_constant__ CUtensorMap m_out, const Params prm) {
    extern __shared__ uint8_t smem_raw[];
    const uint32_t sbase = (smem_u32(smem_raw) + 1023u) & ~1023u;
    const uint32_t bar_full = sbase + OFF_BAR;
    const uint32_t bar_empty = bar_full + 8 * NSTAGE;
    const uint32_t bar_stg_full = bar_empty + 8 * NSTAGE;
    const uint32_t bar_stg_empty = bar_stg_full + 8;
    const uint32_t bar_w = bar_stg_empty + 8;
    const uint32_t bar_phi = bar_w + 8;
    const uint32_t bar_kvd = bar_phi + 8;
    const uint32_t bar_kvx = bar_kvd + 8;
    const uint32_t bar_od = bar_kvx + 8;
    const uint32_t stg = sbase + OFF_STG;

    const int tid = threadIdx.x;
    const int warp = tid >> 5, lane = tid & 31;
    const int cta = blockIdx.x;
    const int r = cta & 1, p = cta >> 1;
    const int hp = p & 15, tg = p >> 4;
    const int tok_a = tg * 4 + r, tok_b = tg * 4 + 2 + r;
    const int ft = p & 15, dt = (p >> 4) * 2 + r;
    const int st = (p & 7) * 2 + r, nt = (p >> 3) & 3, kh = p >> 5;
    const bool ts0 = tg == 0 && r == 0;
    const int nB = kh ? FB - N0 : N0;
    const int l7 = lane & 7, lb3 = (lane >> 3) & 1, lb4 = lane >> 4;
    const unsigned epoch = ld_relaxed(&g_flags[FL_LN * 32]) / NCTA;

    if (tid == 32) {
        asm volatile("prefetch.tensormap [%0];" ::"l"((uint64_t)&m_x) : "memory");
        asm volatile("prefetch.tensormap [%0];" ::"l"((uint64_t)&m_wqkv) : "memory");
        asm volatile("prefetch.tensormap [%0];" ::"l"((uint64_t)&m_h) : "memory");
        asm volatile("prefetch.tensormap [%0];" ::"l"((uint64_t)&m_w1) : "memory");
    }
    if (tid == 256) {
        for (int i = 0; i < NSTAGE; i++) {
            mbar_init(bar_full + 8 * i, 1);
            mbar_init(bar_empty + 8 * i, 8);
        }
        mbar_init(bar_stg_full, 8);
        mbar_init(bar_stg_empty, 1);
        mbar_init(bar_w, 1);
        mbar_init(bar_phi, 1);
        mbar_init(bar_kvd, 8);
        mbar_init(bar_kvx, 1);
        mbar_init(bar_od, 8);
        fence_async_smem();
#pragma unroll 1
        for (int i = 0; i < NSTAGE; i++) {
            mbar_expect_tx(bar_full + 8 * i, BK * 640);
            tma3d(sbase + i * SLOT, &m_x, i * BK, tok_a * 128, 0, bar_full + 8 * i);
            tma3d(sbase + i * SLOT + BOFF, &m_wqkv, hp * 64, i * BK, 0, bar_full + 8 * i);
        }
    }
    __syncthreads();

    if (warp >= 8) {
      asm volatile("setmaxnreg.dec.sync.aligned.u32 120;");
      if (warp == 8) {
        if (lane == 0) {
            uint32_t fb = bar_full, dst = sbase, par = 0;
            auto phase = [&](const CUtensorMap* ma, int a1, int a2, bool a_on_0, const CUtensorMap* mb, int b0, int b2, int k0, uint32_t bytes, int cnt) {
#pragma unroll 1
                for (int i = 0; i < cnt; i++) {
                    mbar_wait<2>(fb + 8 * NSTAGE, par);
                    mbar_expect_tx(fb, bytes);
                    tma3d(dst, ma, a_on_0 ? k0 : 0, a_on_0 ? a1 : k0, a2, fb);
                    tma3d(dst + BOFF, mb, b0, k0, b2, fb);
                    k0 += BK;
                    fb += 8; dst += SLOT;
                    if (fb == bar_full + 8 * NSTAGE) { fb = bar_full; dst = sbase; par ^= 1; }
                }
            };
            auto dep = [&](int flag, unsigned target, int tl) {
                (void)tl;
                wait_flag<2>(&g_flags[flag * 32], target, epoch);
                fence_async_glob();
            };
            phase(&m_x, tok_a * 128, 0, true, &m_wqkv, hp * 64, 0, NSTAGE * BK, BK * 640, 1024 / BK - NSTAGE);
            dep(FL_LN, NCTA, 20);
            phase(&m_h, 0, dt * 2, false, &m_w1, 0, ft * 7, 0, BK * 704, 768 / BK);
            dep(FL_LN1, NCTA, 26);
            phase(&m_h, 0, dt * 2, false, &m_w1, 0, ft * 7, 768, BK * 704, 768 / BK);
            dep(FL_LN2, NCTA, 26);
            phase(&m_h, 0, dt * 2, false, &m_w1, 0, ft * 7, 1536, BK * 704, 512 / BK);
            phase(&m_x, tok_b * 128, 0, true, &m_wqkv, hp * 64, 0, 0, BK * 640, 1024 / BK);
            static_assert(N0 * BK == 8 * 224, "K halves start at an f-tile boundary");
            dep(FL_UF + nt * 2 + kh, 2, 22);
            phase(&m_w2, 0, st * 2, false, &m_u, 0, nt * 4, kh ? N0 * BK : 0, BK * 768, 192 / BK);
            dep(FL_U + nt, 32, 28);
            phase(&m_w2, 0, st * 2, false, &m_u, 0, nt * 4, (kh ? N0 * BK : 0) + 192, BK * 768, nB - 192 / BK);
            dep(FL_O + st * 2 + kh, 8, 24);
            phase(&m_o, 0, st * 2, false, &m_wo, 0, nt * 4, kh ? 512 : 0, BK * 768, 512 / BK);
        }
      } else {
        const int et = tid - 288, sw = warp - 9;
        const int g8 = lane >> 2, t4 = lane & 3;
        {
            if (ts0) {
#pragma unroll
                for (int i = 0; i < 16; i++) g_kvsum[(hp * 16 + i) * 96 + et] = make_float4(0.f, 0.f, 0.f, 0.f);
            }
#pragma unroll 1
            for (int b = 0; b < 3; b++) {
                const int row0 = b * 768 + cta * (b < 2 ? 6 : 4) + sw * 2;
                if (b < 2 || sw < 2) ln_rows<2>(prm.x, prm.gate_w, row0, row0 + 2, lane);
                if (b == 0) {
                    for (int idx = et; idx < 256; idx += 96) {
                        const int k = (idx >> 2) & 31, u = idx & 3, h = idx >> 7;
                        sts128(sbase + OFF_WPHI + h * 4096 + k * 128 + ((u ^ (k & 7)) << 4),
                               __ldg((const uint4*)(prm.wphi + ((size_t)(hp * 2 + h) * 32 + k) * 32 + u * 8)));
                    }
                    fence_async_smem();
                }
                fence_async_glob();
                bar_sync(1, 96);
                if (et == 0) {
                    if (b == 0) mbar_arrive(bar_w);
                    flag_add(&g_flags[(b == 0 ? FL_LN : b == 1 ? FL_LN1 : FL_LN2) * 32]);
                }
            }
        }

#pragma unroll 1
        for (int tile = 0; tile < 2; tile++) {
            if (tile) {
                mbar_wait<1>(bar_stg_full, 1);
#pragma unroll 1
                for (int idx = et; idx < 896; idx += 96) {
                    uint4 a[4];
                    __nv_bfloat162 b[4];
                    const int u = idx & 15;
#pragma unroll
                    for (int h = 0; h < 4; h++) {
                        const int row = (idx >> 4) + h * 56;
                        a[h] = lds128(stg + row * 256 + ((u ^ (row & 7)) << 4));
                        b[h] = __bfloat162bfloat162(__ldg(prm.b1 + ft * 224 + row));
                    }
#pragma unroll
                    for (int h = 0; h < 4; h++) {
                        const int row = (idx >> 4) + h * 56;
                        const uint32_t av[4] = {a[h].x, a[h].y, a[h].z, a[h].w};
                        uint32_t ov[4];
#pragma unroll
                        for (int k = 0; k < 4; k++) {
                            const __nv_bfloat162 ts2 = __hadd2(*(const __nv_bfloat162*)&av[k], b[h]);
                            const uint32_t tsum = *(const uint32_t*)&ts2;
                            ov[k] = h < GH ? av[k] : pack2(gelu_tanh(bf_lo(tsum)), gelu_tanh(bf_hi(tsum)));
                        }
                        *(uint4*)(g_u + (size_t)(ft * 224 + row) * D_ + dt * 128 + u * 8) = make_uint4(ov[0], ov[1], ov[2], ov[3]);
                    }
                }
                fence_async_glob();
                bar_sync(1, 96);
                if (et == 0) {
                    mbar_arrive(bar_stg_empty);
                    flag_add(&g_flags[(FL_U + (dt >> 1)) * 32]);
                    if ((ft & 7) == 0) asm volatile("red.relaxed.gpu.global.add.u32 [%0], 1;" ::"l"(&g_flags[(FL_UF + (dt >> 1) * 2 + (ft >> 3)) * 32]) : "memory");
                }
            }
            mbar_wait<1>(bar_stg_full, 0);
            for (int idx = et; idx < 256; idx += 96)
                sts128(stg + 32768 + idx * 128 + ((4 ^ (idx & 7)) << 4), make_uint4(0x3F803F80u, 0x3F803F80u, 0x3F803F80u, 0x3F803F80u));
#pragma unroll 1
            for (int it = sw * 2; it < 16; it += (it & 1) ? 5 : 1) {
                const int rb = it >> 1, which = it & 1;
                const uint32_t rowa = stg + (rb * 16 + l7 + lb3 * 8) * 128;
                uint32_t pk[4][4], P[4][4], M[4][4];
#pragma unroll
                for (int j = 0; j < 4; j++)
                    ldsm4(rowa + which * 16384 + (((j * 2 + lb4) ^ l7) << 4), pk[(j >> 1) * 2][(j & 1) * 2], pk[(j >> 1) * 2 + 1][(j & 1) * 2],
                          pk[(j >> 1) * 2][(j & 1) * 2 + 1], pk[(j >> 1) * 2 + 1][(j & 1) * 2 + 1]);
                dual_softmax<4>(pk, P, M);
                if (which == 0) {
                    uint4* dst = &g_pq[(size_t)((cta * 16 + tile * 8 + rb) * 8) * 32 + lane];
#pragma unroll
                    for (int hh = 0; hh < 2; hh++) {
                        dst[(hh * 4 + 0) * 32] = make_uint4(P[2 * hh][0], P[2 * hh + 1][0], P[2 * hh][1], P[2 * hh + 1][1]);
                        dst[(hh * 4 + 1) * 32] = make_uint4(P[2 * hh][2], P[2 * hh + 1][2], P[2 * hh][3], P[2 * hh + 1][3]);
                        dst[(hh * 4 + 2) * 32] = make_uint4(M[2 * hh][0], M[2 * hh + 1][0], M[2 * hh][1], M[2 * hh + 1][1]);
                        dst[(hh * 4 + 3) * 32] = make_uint4(M[2 * hh][2], M[2 * hh + 1][2], M[2 * hh][3], M[2 * hh + 1][3]);
                    }
                } else {
#pragma unroll
                    for (int hh = 0; hh < 2; hh++) {
                        const uint32_t base = rowa + hh * 16384;
                        stmatrix4(base + (((0 + lb4) ^ l7) << 4), P[2 * hh][0], P[2 * hh + 1][0], P[2 * hh][1], P[2 * hh + 1][1]);
                        stmatrix4(base + (((2 + lb4) ^ l7) << 4), P[2 * hh][2], P[2 * hh + 1][2], P[2 * hh][3], P[2 * hh + 1][3]);
                        stmatrix4(base + (((4 + lb4) ^ l7) << 4), M[2 * hh][0], M[2 * hh + 1][0], M[2 * hh][1], M[2 * hh + 1][1]);
                        stmatrix4(base + (((6 + lb4) ^ l7) << 4), M[2 * hh][2], M[2 * hh + 1][2], M[2 * hh][3], M[2 * hh + 1][3]);
                    }
                }
            }
            fence_async_smem();
            if (tile == 0 && et == 0) wait_flag<1>(&g_flags[FL_LN * 32], NCTA, epoch);
            bar_sync(1, 96);
            if (et == 0) mbar_arrive(bar_phi);
        }
        if (et == 0) {
            mbar_wait<1>(bar_kvd, 1);
            flag_add(&g_flags[(FL_KV + hp) * 32]);
            wait_flag<1>(&g_flags[(FL_KV + hp) * 32], 8, epoch);
        }
        bar_sync(1, 96);
#pragma unroll
        for (int hh = 0; hh < 2; hh++) {
            float4 sv[8];
#pragma unroll
            for (int i = 0; i < 8; i++) sv[i] = __ldcg(&g_kvsum[((hp * 2 + hh) * 8 + i) * 96 + et]);
            const uint32_t base = stg + 32768 + hh * 8192 + (sw * 16 + g8) * 128 + t4 * 4;
#pragma unroll
            for (int i = 0; i < 8; i++) {
                sts32(base + ((i ^ g8) << 4), pack2(sv[i].x, sv[i].y));
                if (sw < 2) sts32(base + 1024 + ((i ^ g8) << 4), pack2(sv[i].z, sv[i].w));
            }
        }
        fence_async_smem();
        bar_sync(1, 96);
        if (et == 0) {
            mbar_arrive(bar_kvx);
            mbar_wait<1>(bar_od, 0);
            tma3d_store(&m_os, stg, 0, hp * 64, tok_a * 2);
            tma3d_store(&m_os, stg + 16384, 0, hp * 64, tok_b * 2);
            bulk_commit();
            bulk_wait_all();
            fence_async_glob();
            flag_add(&g_flags[(FL_O + tok_a * 2 + (hp >> 3)) * 32]);
            asm volatile("red.relaxed.gpu.global.add.u32 [%0], 1;" ::"l"(&g_flags[(FL_O + tok_b * 2 + (hp >> 3)) * 32]) : "memory");
        }
      }
    } else {
        asm volatile("setmaxnreg.inc.sync.aligned.u32 192;");
        const int wg = warp >> 2, wq = warp & 3;
        const int mrow = wg * 64 + wq * 16 + lb3 * 8 + l7;
        Ring ring{0, 0};
        auto kv_section = [&](uint32_t parity) {
            mbar_wait<0>(bar_phi, parity);
            float c[32];
            zero(c);
            pin(c);
            wgmma_fence();
#pragma unroll
            for (int ks = 0; ks < 8; ks++)
                wgmma_n64<1, 1>(c, mkdesc(stg + 32768 + wg * 16384 + ks * 2048, 8192, 1024, 1), mkdesc(stg + wg * 16384 + ks * 2048, 8192, 1024, 1), 1);
            wgmma_commit();
            wgmma_wait<0>();
            pin(c);
            if (wq < 3) {
#pragma unroll
                for (int i = 0; i < 8; i++)
                    red_add4(&g_kvsum[((hp * 2 + wg) * 8 + i) * 96 + wq * 32 + lane],
                             make_float4(c[4 * i], c[4 * i + 1], wq == 2 ? 0.f : c[4 * i + 2], wq == 2 ? 0.f : c[4 * i + 3]));
            }
            __syncwarp();
            if (lane == 0) mbar_arrive(bar_kvd);
        };

#pragma unroll 1
        for (int pass = 0; pass < 2; pass++) {
            {
                float acc[96];
                zero(acc);
                mainloop<0>(acc, 1024 / BK, ring, sbase, bar_full, bar_empty, wg, lane);
                mbar_wait<0>(pass ? bar_stg_empty : bar_w, 0);
                float pf[4][16];
                {
                    uint32_t a[8][4];
#pragma unroll
                    for (int j = 0; j < 8; j++) {
                        a[j][0] = pack2(acc[8 * j], acc[8 * j + 1]); a[j][1] = pack2(acc[8 * j + 2], acc[8 * j + 3]);
                        a[j][2] = pack2(acc[8 * j + 4], acc[8 * j + 5]); a[j][3] = pack2(acc[8 * j + 6], acc[8 * j + 7]);
                    }
                    zero(pf[0]); zero(pf[1]); zero(pf[2]); zero(pf[3]);
                    pin(pf[0]); pin(pf[1]); pin(pf[2]); pin(pf[3]);
#pragma unroll
                    for (int j = 0; j < 8; j++) { pin(a[j][0]); pin(a[j][1]); pin(a[j][2]); pin(a[j][3]); }
                    wgmma_fence();
#pragma unroll
                    for (int j = 0; j < 8; j++)
                        wgmma_rs_n32<1>(pf[j >> 1], a[j][0], a[j][1], a[j][2], a[j][3], mkdesc(sbase + OFF_WPHI + (j & 3) * 2048, 4096, 1024, 1), 1);
                    wgmma_commit();
                }
                const uint32_t base = stg + mrow * 128;
#pragma unroll
                for (int j = 0; j < 4; j++)
                    stmatrix4(base + 32768 + (j >> 1) * 16384 + ((((j & 1) * 2 + lb4) ^ l7) << 4),
                              pack2(acc[64 + 8 * j], acc[65 + 8 * j]), pack2(acc[66 + 8 * j], acc[67 + 8 * j]),
                              pack2(acc[68 + 8 * j], acc[69 + 8 * j]), pack2(acc[70 + 8 * j], acc[71 + 8 * j]));
                wgmma_wait<0>();
#pragma unroll
                for (int j = 0; j < 8; j++) {
                    const float* f = &pf[j >> 1][(j & 1) * 8];
                    stmatrix4(base + (j >> 2) * 16384 + ((((j & 3) * 2 + lb4) ^ l7) << 4),
                              pack2(f[0], f[1]), pack2(f[2], f[3]), pack2(f[4], f[5]), pack2(f[6], f[7]));
                }
                fence_async_smem();
                __syncwarp();
                if (lane == 0) mbar_arrive(bar_stg_full);
            }
            if (pass == 0) {
                float acc[112];
                zero(acc);
#pragma unroll 1
                for (int half = 0; half < 2; half++) {
                    mainloop<1>(acc, half ? (2048 - KVA) / BK : KVA / BK, ring, sbase, bar_full, bar_empty, wg, lane);
                    if (half == 0) kv_section(0);
                }
                mbar_wait<0>(bar_kvd, 0);
                const uint32_t base = stg + (lb4 * 8 + l7) * 256 + (((wg * 8 + wq * 2 + lb3) ^ l7) << 4);
                uint32_t pk[56];
#pragma unroll
                for (int i = 0; i < 56; i++) pk[i] = pack2(acc[2 * i], acc[2 * i + 1]);
#pragma unroll
                for (int b = 0; b < 7 * GH; b++) {
                    const __nv_bfloat162 bb = __ldg((const __nv_bfloat162*)(prm.b1 + ft * 224 + b * 8 + (lane & 3) * 2));
#pragma unroll
                    for (int h = 0; h < 2; h++) {
                        const __nv_bfloat162 t2 = __hadd2(*(const __nv_bfloat162*)&pk[2 * b + h], bb);
                        const uint32_t t = *(const uint32_t*)&t2;
                        pk[2 * b + h] = pack2(gelu_tanh(bf_lo(t)), gelu_tanh(bf_hi(t)));
                    }
                }
#pragma unroll
                for (int jb = 0; jb < 14; jb++) stmatrix4t(base + jb * 4096, pk[4 * jb], pk[4 * jb + 1], pk[4 * jb + 2], pk[4 * jb + 3]);
                __syncwarp();
                if (lane == 0) mbar_arrive(bar_stg_full);
            }
        }
        float acc[128];
        zero(acc);
        const int grow = st * 128 + wg * 64 + wq * 16 + (lane >> 2);
        mainloop<2>(acc, S1, ring, sbase, bar_full, bar_empty, wg, lane);
        kv_section(1);
        mainloop<2>(acc, S2 - S1, ring, sbase, bar_full, bar_empty, wg, lane);
        {
            const uint4* src = &g_pq[(size_t)((cta * 16 + wg * 8 + wq) * 8) * 32 + lane];
            const int orow = (wg ? tok_b : tok_a) * 128 + wq * 16 + (lane >> 2);
            uint4 qn[4];
#pragma unroll
            for (int i = 0; i < 4; i++) qn[i] = __ldcg(src + i * 32);
            const float ga0 = __ldcg(&g_gate[orow]), ga1 = __ldcg(&g_gate[orow + 8]);
            const float gb0 = __ldcg(&g_gate[orow + 64]), gb1 = __ldcg(&g_gate[orow + 72]);
            mbar_wait<0>(bar_kvx, 0);
#pragma unroll 1
            for (int un = 0; un < 4; un++) {
                const int mb = un >> 1, hh = un & 1;
                uint4 q[4];
#pragma unroll
                for (int i = 0; i < 4; i++) q[i] = qn[i];
                if (un < 3) {
                    const uint4* nsrc = src + (((un + 1) >> 1) * 32 + ((un + 1) & 1) * 4) * 32;
#pragma unroll
                    for (int i = 0; i < 4; i++) qn[i] = __ldcg(nsrc + i * 32);
                }
                const float gt0 = mb ? gb0 : ga0, gt1 = mb ? gb1 : ga1;
                float o[20];
                zero(o);
                pin(o);
#pragma unroll
                for (int i = 0; i < 4; i++) { pin(q[i].x); pin(q[i].y); pin(q[i].z); pin(q[i].w); }
                wgmma_fence();
#pragma unroll
                for (int j = 0; j < 4; j++)
                    wgmma_rs_n40<0>(o, q[j].x, q[j].y, q[j].z, q[j].w, mkdesc(stg + 32768 + hh * 8192 + j * 32, 16, 1024, 1), 1);
                wgmma_commit();
                wgmma_wait<0>();
                pin(o);
#pragma unroll
                for (int i = 0; i < 4; i++) { pin(q[i].x); pin(q[i].y); pin(q[i].z); pin(q[i].w); }
                const float s0 = gt0 * rcp_fast(o[16] + 1e-6f), s1 = gt1 * rcp_fast(o[18] + 1e-6f);
                const uint32_t base = stg + wg * 16384 + mb * 8192 + (hh * 32 + lb4 * 8 + l7) * 128 + (((wq * 2 + lb3) ^ l7) << 4);
                stmatrix4t(base, pack2(o[0] * s0, o[1] * s0), pack2(o[2] * s1, o[3] * s1),
                           pack2(o[4] * s0, o[5] * s0), pack2(o[6] * s1, o[7] * s1));
                stmatrix4t(base + 2048, pack2(o[8] * s0, o[9] * s0), pack2(o[10] * s1, o[11] * s1),
                           pack2(o[12] * s0, o[13] * s0), pack2(o[14] * s1, o[15] * s1));
            }
            fence_async_smem();
            __syncwarp();
            if (lane == 0) mbar_arrive(bar_od);
        }
        mainloop<2>(acc, nB - S2, ring, sbase, bar_full, bar_empty, wg, lane);
        {
            const float c0 = 1.f - __ldcg(&g_gate[grow]), c1 = 1.f - __ldcg(&g_gate[grow + 8]);
            const float b0 = kh ? __bfloat162float(prm.b2[grow]) : 0.f, b1v = kh ? __bfloat162float(prm.b2[grow + 8]) : 0.f;
#pragma unroll
            for (int i = 0; i < 32; i++) {
                acc[4 * i] = (acc[4 * i] + b0) * c0;
                acc[4 * i + 1] = (acc[4 * i + 1] + b0) * c0;
                acc[4 * i + 2] = (acc[4 * i + 2] + b1v) * c1;
                acc[4 * i + 3] = (acc[4 * i + 3] + b1v) * c1;
            }
        }
        mainloop<2>(acc, 512 / BK, ring, sbase, bar_full, bar_empty, wg, lane);
        {
            const int tile = st * 4 + nt;
            uint4* dst = &g_part[(size_t)(tile * 2 + kh) * 8 * 256 + tid];
#pragma unroll
            for (int i = 0; i < 8; i++) {
                uint32_t v[4];
#pragma unroll
                for (int k = 0; k < 4; k++)
                    v[k] = kh ? pack2(acc[8 * i + 2 * k], acc[8 * i + 2 * k + 1]) : pack2(acc[64 + 8 * i + 2 * k], acc[65 + 8 * i + 2 * k]);
                dst[i * 256] = make_uint4(v[0], v[1], v[2], v[3]);
            }
            bar_sync(2, 256);
            if (tid == 0) {
                flag_add(&g_flags[(FL_PART + tile * 2 + kh) * 32]);
                wait_flag<0>(&g_flags[(FL_PART + tile * 2 + (kh ^ 1)) * 32], 1, epoch);
            }
            bar_sync(2, 256);
            const uint4* src = &g_part[(size_t)(tile * 2 + (kh ^ 1)) * 8 * 256 + tid];
            uint4 pv[8];
#pragma unroll
            for (int i = 0; i < 8; i++) pv[i] = __ldcg(src + i * 256);
            const uint32_t obase = sbase + wg * 16384 + (wq * 16 + lb3 * 8 + l7) * 128;
#pragma unroll
            for (int i = 0; i < 8; i++) {
                float f[8];
#pragma unroll
                for (int k = 0; k < 8; k++) f[k] = kh ? acc[64 + 8 * i + k] : acc[8 * i + k];
                stmatrix4(obase + (i >> 2) * 8192 + (((((2 * i) & 7) + lb4) ^ l7) << 4),
                          pack2(f[0] + bf_lo(pv[i].x), f[1] + bf_hi(pv[i].x)), pack2(f[2] + bf_lo(pv[i].y), f[3] + bf_hi(pv[i].y)),
                          pack2(f[4] + bf_lo(pv[i].z), f[5] + bf_hi(pv[i].z)), pack2(f[6] + bf_lo(pv[i].w), f[7] + bf_hi(pv[i].w)));
            }
            fence_async_smem();
            bar_sync(3 + wg, 128);
            if ((tid & 127) == 0) {
#pragma unroll
                for (int c = 0; c < 2; c++)
                    tma2d_store(&m_out, sbase + wg * 16384 + c * 8192, nt * 256 + kh * 128 + c * 64, st * 128 + wg * 64);
                bulk_commit();
                bulk_wait_read();
            }
        }
    }
}

typedef CUresult (*EncodeFn)(CUtensorMap*, CUtensorMapDataType, cuuint32_t, void*, const cuuint64_t*, const cuuint64_t*,
                             const cuuint32_t*, const cuuint32_t*, CUtensorMapInterleave, CUtensorMapSwizzle,
                             CUtensorMapL2promotion, CUtensorMapFloatOOBfill);

void make_map(EncodeFn enc, CUtensorMap* m, const void* ptr, int rank, const uint64_t* dims, const uint64_t* strides_bytes,
              const uint32_t* box, CUtensorMapSwizzle swz) {
    cuuint64_t gd[3], gs[2];
    cuuint32_t bd[3], es[3] = {1, 1, 1};
    for (int i = 0; i < rank; i++) { gd[i] = dims[i]; bd[i] = box[i]; }
    for (int i = 0; i < rank - 1; i++) gs[i] = strides_bytes[i];
    CUresult res = enc(m, CU_TENSOR_MAP_DATA_TYPE_BFLOAT16, rank, const_cast<void*>(ptr), gd, gs, bd, es, CU_TENSOR_MAP_INTERLEAVE_NONE, swz,
        CU_TENSOR_MAP_L2_PROMOTION_L2_128B, CU_TENSOR_MAP_FLOAT_OOB_FILL_NONE);
    (void)res;
}

}

extern "C" void kernel_launch(void* const* d_in, const int* in_sizes, int n_in, void* d_out, int out_size) {
    (void)in_sizes; (void)n_in; (void)out_size;
    const __nv_bfloat16* x = (const __nv_bfloat16*)d_in[0];
    const __nv_bfloat16* wqkv = (const __nv_bfloat16*)d_in[1];
    const __nv_bfloat16* wphi = (const __nv_bfloat16*)d_in[2];
    const __nv_bfloat16* wo = (const __nv_bfloat16*)d_in[3];
    const __nv_bfloat16* w1 = (const __nv_bfloat16*)d_in[5];
    const __nv_bfloat16* b1 = (const __nv_bfloat16*)d_in[6];
    const __nv_bfloat16* w2 = (const __nv_bfloat16*)d_in[7];
    const __nv_bfloat16* b2 = (const __nv_bfloat16*)d_in[8];
    const __nv_bfloat16* gate_w = (const __nv_bfloat16*)d_in[9];

    EncodeFn enc = nullptr;
    cudaDriverEntryPointQueryResult qr;
    cudaGetDriverEntryPoint("cuTensorMapEncodeTiled", (void**)&enc, cudaEnableDefault, &qr);
    void *p_h, *p_u, *p_o;
    cudaGetSymbolAddress(&p_h, g_h);
    cudaGetSymbolAddress(&p_u, g_u);
    cudaGetSymbolAddress(&p_o, g_o);

    CUtensorMap m_x, m_wqkv, m_h, m_w1, m_w2, m_u, m_o, m_wo, m_os, m_out;
    {
        uint64_t d[3] = {1024, 2048, 1}, s[2] = {2048, 2048 * 2048};
        uint32_t b[3] = {BK, 128, 1};
        make_map(enc, &m_x, x, 3, d, s, b, BK == 64 ? CU_TENSOR_MAP_SWIZZLE_128B : CU_TENSOR_MAP_SWIZZLE_64B);
    }
    {
        uint64_t d[2] = {1024, 2048}, s[1] = {2048};
        uint32_t b[2] = {64, 64};
        make_map(enc, &m_out, d_out, 2, d, s, b, CU_TENSOR_MAP_SWIZZLE_128B);
    }
    {
        uint64_t d[3] = {1024, 1024, 3}, s[2] = {6144, 2048};
        uint32_t b[3] = {64, BK, 3};
        make_map(enc, &m_wqkv, wqkv, 3, d, s, b, CU_TENSOR_MAP_SWIZZLE_128B);
    }
    {
        uint64_t d[3] = {64, 2048, 16}, s[2] = {2048, 128};
        uint32_t b[3] = {64, BK, 2};
        make_map(enc, &m_h, p_h, 3, d, s, b, CU_TENSOR_MAP_SWIZZLE_128B);
    }
    {
        uint64_t d[3] = {32, 2048, 112}, s[2] = {7168, 64};
        uint32_t b[3] = {32, BK, 7};
        make_map(enc, &m_w1, w1, 3, d, s, b, CU_TENSOR_MAP_SWIZZLE_64B);
    }
    {
        uint64_t d[3] = {64, 3584, 32}, s[2] = {4096, 128};
        uint32_t b[3] = {64, BK, 2};
        make_map(enc, &m_w2, w2, 3, d, s, b, CU_TENSOR_MAP_SWIZZLE_128B);
    }
    {
        uint64_t d[3] = {64, 3584, 16}, s[2] = {2048, 128};
        uint32_t b[3] = {64, BK, 4};
        make_map(enc, &m_u, p_u, 3, d, s, b, CU_TENSOR_MAP_SWIZZLE_128B);
    }
    {
        uint64_t d[3] = {64, 1024, 32}, s[2] = {4096, 128};
        uint32_t b[3] = {64, BK, 2};
        make_map(enc, &m_o, p_o, 3, d, s, b, CU_TENSOR_MAP_SWIZZLE_128B);
        uint32_t bs[3] = {64, 64, 2};
        make_map(enc, &m_os, p_o, 3, d, s, bs, CU_TENSOR_MAP_SWIZZLE_128B);
    }
    {
        uint64_t d[3] = {64, 1024, 16}, s[2] = {2048, 128};
        uint32_t b[3] = {64, BK, 4};
        make_map(enc, &m_wo, wo, 3, d, s, b, CU_TENSOR_MAP_SWIZZLE_128B);
    }
    Params prm{x, wphi, b1, b2, gate_w};

    cudaFuncSetAttribute(fused_kernel, cudaFuncAttributeMaxDynamicSharedMemorySize, SMEM_BYTES);
    fused_kernel<<<NCTA, NTHREADS, SMEM_BYTES, cudaStreamPerThread>>>(m_x, m_wqkv, m_h, m_w1, m_w2, m_u, m_o, m_wo, m_os, m_out, prm);
}
```

```cpp
#include <cuda_runtime.h>
#include <cuda.h>
#include <cuda_bf16.h>
#include <stdint.h>

namespace {

constexpr int S_ = 2048, D_ = 1024, F_ = 3584;
constexpr int NCTA = 128;
#define BK_ 32
constexpr int BK = BK_;
constexpr int NSTAGE = 192 / BK;
constexpr int SLOT = BK * 768;
constexpr int BOFF = BK * 256;
constexpr int OFF_STG = NSTAGE * SLOT;
constexpr int OFF_WPHI = OFF_STG + 65536;
constexpr int OFF_BAR = OFF_WPHI + 8192;
constexpr int SMEM_BYTES = OFF_BAR + 256 + 1024;
#define N0_ 28
constexpr int N0 = N0_ * (64 / BK);
constexpr int FB = F_ / BK;
constexpr int NTHREADS = 384;
#define KVA_ 1792
constexpr int KVA = KVA_;
#define GH_ 0
constexpr int GH = GH_;
#define S1_ 14
#define S2_ 20
constexpr int S1 = S1_ * (64 / BK), S2 = S2_ * (64 / BK);

constexpr int FL_LN = 0, FL_U = 1, FL_KV = 5, FL_O = 21, FL_PART = 53, FL_LN1 = 181, FL_LN2 = 182, FL_UF = 183, FL_COUNT = 191;

__device__ __align__(1024) __nv_bfloat16 g_h[S_ * D_];
__device__ __align__(1024) __nv_bfloat16 g_u[F_ * D_];
__device__ __align__(1024) __nv_bfloat16 g_o[D_ * S_];
__device__ __align__(1024) uint4 g_pq[NCTA * 16 * 8 * 32];
__device__ __align__(1024) float4 g_kvsum[16 * 2 * 8 * 96];
__device__ __align__(1024) uint4 g_part[64 * 16 * 256];
__device__ __align__(1024) float g_gate[S_];
__device__ __align__(1024) unsigned g_flags[FL_COUNT * 32];

__device__ __forceinline__ uint32_t smem_u32(const void* p) { return (uint32_t)__cvta_generic_to_shared(p); }
__device__ __forceinline__ void mbar_init(uint32_t bar, uint32_t cnt) {
    asm volatile("mbarrier.init.shared::cta.b64 [%0], %1;" ::"r"(bar), "r"(cnt));
}
__device__ __forceinline__ void mbar_expect_tx(uint32_t bar, uint32_t bytes) {
    asm volatile("mbarrier.arrive.expect_tx.shared::cta.b64 _, [%0], %1;" ::"r"(bar), "r"(bytes) : "memory");
}
__device__ __forceinline__ void mbar_arrive(uint32_t bar) {
    asm volatile("mbarrier.arrive.shared::cta.b64 _, [%0];" ::"r"(bar) : "memory");
}
__device__ __forceinline__ bool elect_one() {
    uint32_t pred;
    asm volatile("{\n.reg .pred p;\nelect.sync _|p, 0xffffffff;\nselp.u32 %0, 1, 0, p;\n}" : "=r"(pred));
    return pred != 0;
}
template <int ROLE>
__device__ __forceinline__ void mbar_wait(uint32_t bar, uint32_t parity) {
    uint32_t done;
    int n = 0;
    while (true) {
        asm volatile("{\n.reg .pred p;\nmbarrier.try_wait.parity.shared::cta.b64 p, [%1], %2;\nselp.u32 %0, 1, 0, p;\n}"
                     : "=r"(done) : "r"(bar), "r"(parity) : "memory");
        if (done || ++n >= (1 << 22)) break;
    }
}
__device__ __forceinline__ unsigned ld_relaxed(const unsigned* p) {
    unsigned v;
    asm volatile("ld.relaxed.gpu.global.u32 %0, [%1];" : "=r"(v) : "l"(p) : "memory");
    return v;
}
template <int ROLE>
__device__ __forceinline__ void wait_flag(const unsigned* p, unsigned target, unsigned epoch) {
    unsigned v;
    int n = 0;
    const unsigned base = epoch * target;
    while (true) {
        asm volatile("ld.acquire.gpu.global.u32 %0, [%1];" : "=r"(v) : "l"(p) : "memory");
        if (v - base >= target) break;
        if (++n > (1 << 20)) break;
        __nanosleep(40);
    }
}
__device__ __forceinline__ void flag_add(unsigned* p) {
    asm volatile("red.release.gpu.global.add.u32 [%0], 1;" ::"l"(p) : "memory");
}
__device__ __forceinline__ void fence_async_smem() { asm volatile("fence.proxy.async.shared::cta;" ::: "memory"); }
__device__ __forceinline__ void fence_async_glob() { asm volatile("fence.proxy.async.global;" ::: "memory"); }
__device__ __forceinline__ void bar_sync(int id, int n) {
    __syncwarp();
    asm volatile("bar.sync %0, %1;" ::"r"(id), "r"(n) : "memory");
}

__device__ __forceinline__ void tma3d(uint32_t dst, const CUtensorMap* m, int c0, int c1, int c2, uint32_t bar) {
    asm volatile("cp.async.bulk.tensor.3d.shared::cluster.global.mbarrier::complete_tx::bytes [%0], [%1, {%3, %4, %5}], [%2];"
                 ::"r"(dst), "l"((uint64_t)m), "r"(bar), "r"(c0), "r"(c1), "r"(c2) : "memory");
}
__device__ __forceinline__ void tma2d_store(const CUtensorMap* m, uint32_t src, int c0, int c1) {
    asm volatile("cp.async.bulk.tensor.2d.global.shared::cta.bulk_group [%0, {%2, %3}], [%1];"
                 ::"l"((uint64_t)m), "r"(src), "r"(c0), "r"(c1) : "memory");
}
__device__ __forceinline__ void tma3d_store(const CUtensorMap* m, uint32_t src, int c0, int c1, int c2) {
    asm volatile("cp.async.bulk.tensor.3d.global.shared::cta.bulk_group [%0, {%2, %3, %4}], [%1];"
                 ::"l"((uint64_t)m), "r"(src), "r"(c0), "r"(c1), "r"(c2) : "memory");
}
__device__ __forceinline__ void bulk_commit() { asm volatile("cp.async.bulk.commit_group;" ::: "memory"); }
__device__ __forceinline__ void bulk_wait_all() { asm volatile("cp.async.bulk.wait_group 0;" ::: "memory"); }
__device__ __forceinline__ void bulk_wait_read() { asm volatile("cp.async.bulk.wait_group.read 0;" ::: "memory"); }

__device__ __forceinline__ void wgmma_fence() { asm volatile("wgmma.fence.sync.aligned;" ::: "memory"); }
__device__ __forceinline__ void wgmma_commit() { asm volatile("wgmma.commit_group.sync.aligned;" ::: "memory"); }
template <int N>
__device__ __forceinline__ void wgmma_wait() { asm volatile("wgmma.wait_group.sync.aligned %0;" ::"n"(N) : "memory"); }

__device__ __forceinline__ uint64_t mkdesc(uint32_t addr, uint32_t lbo, uint32_t sbo, uint32_t swz) {
    return (uint64_t)((addr & 0x3FFFF) >> 4) | ((uint64_t)(lbo >> 4) << 16) | ((uint64_t)(sbo >> 4) << 32) | ((uint64_t)swz << 62);
}
__device__ __forceinline__ uint32_t pack2(float lo, float hi) {
    uint32_t r;
    asm("cvt.rn.bf16x2.f32 %0, %1, %2;" : "=r"(r) : "f"(hi), "f"(lo));
    return r;
}
__device__ __forceinline__ float bf_lo(uint32_t v) { return __uint_as_float(v << 16); }
__device__ __forceinline__ float bf_hi(uint32_t v) { return __uint_as_float(v & 0xFFFF0000u); }
__device__ __forceinline__ void stmatrix4(uint32_t addr, uint32_t r0, uint32_t r1, uint32_t r2, uint32_t r3) {
    asm volatile("stmatrix.sync.aligned.m8n8.x4.shared.b16 [%0], {%1, %2, %3, %4};" ::"r"(addr), "r"(r0), "r"(r1), "r"(r2), "r"(r3) : "memory");
}
__device__ __forceinline__ void stmatrix4t(uint32_t addr, uint32_t r0, uint32_t r1, uint32_t r2, uint32_t r3) {
    asm volatile("stmatrix.sync.aligned.m8n8.x4.trans.shared.b16 [%0], {%1, %2, %3, %4};" ::"r"(addr), "r"(r0), "r"(r1), "r"(r2), "r"(r3) : "memory");
}
__device__ __forceinline__ void ldsm4(uint32_t addr, uint32_t& r0, uint32_t& r1, uint32_t& r2, uint32_t& r3) {
    asm volatile("ldmatrix.sync.aligned.m8n8.x4.shared.b16 {%0, %1, %2, %3}, [%4];" : "=r"(r0), "=r"(r1), "=r"(r2), "=r"(r3) : "r"(addr) : "memory");
}
__device__ __forceinline__ uint4 lds128(uint32_t addr) {
    uint4 v;
    asm volatile("ld.shared.v4.u32 {%0, %1, %2, %3}, [%4];" : "=r"(v.x), "=r"(v.y), "=r"(v.z), "=r"(v.w) : "r"(addr) : "memory");
    return v;
}
__device__ __forceinline__ void sts128(uint32_t addr, uint4 v) {
    asm volatile("st.shared.v4.u32 [%0], {%1, %2, %3, %4};" ::"r"(addr), "r"(v.x), "r"(v.y), "r"(v.z), "r"(v.w) : "memory");
}
__device__ __forceinline__ void sts32(uint32_t addr, uint32_t v) {
    asm volatile("st.shared.u32 [%0], %1;" ::"r"(addr), "r"(v) : "memory");
}
__device__ __forceinline__ float ex2(float x) {
    float r;
    asm("ex2.approx.ftz.f32 %0, %1;" : "=f"(r) : "f"(x));
    return r;
}
__device__ __forceinline__ float rcp_fast(float x) {
    float r;
    asm("rcp.approx.ftz.f32 %0, %1;" : "=f"(r) : "f"(x));
    return r;
}
__device__ __forceinline__ void red_add4(float4* p, float4 v) {
    asm volatile("red.relaxed.gpu.global.add.v4.f32 [%0], {%1, %2, %3, %4};" ::"l"(p), "f"(v.x), "f"(v.y), "f"(v.z), "f"(v.w) : "memory");
}
__device__ __forceinline__ float tanh_fast(float x) {
    float r;
    asm("tanh.approx.f32 %0, %1;" : "=f"(r) : "f"(x));
    return r;
}
__device__ __forceinline__ float gelu_tanh(float u) {
    const float z = u * fmaf(u * u, 0.7978845608028654f * 0.044715f, 0.7978845608028654f);
    const float hu = 0.5f * u;
    return fmaf(hu, tanh_fast(z), hu);
}

template <int N>
__device__ __forceinline__ void zero(float (&a)[N]) {
#pragma unroll
    for (int i = 0; i < N; i++) a[i] = 0.f;
}

template <int N>
__device__ __forceinline__ void pin(float (&a)[N]) {
#pragma unroll
    for (int i = 0; i < N; i++) asm volatile("" : "+f"(a[i])::"memory");
}
__device__ __forceinline__ void pin(uint32_t& a) { asm volatile("" : "+r"(a)::"memory"); }

template <int TA, int TB>
__device__ __forceinline__ void wgmma_n192(float (&d)[96], uint64_t da, uint64_t db, int scale_d) {
    asm volatile("{\n.reg .pred p;\nsetp.ne.b32 p, %98, 0;\n"
        "wgmma.mma_async.sync.aligned.m64n192k16.f32.bf16.bf16 {%0, %1, %2, %3, %4, %5, %6, %7, %8, %9, %10, %11, %12, %13, %14, %15, %16, %17, %18, %19, %20, %21, %22, %23, %24, %25, %26, %27, %28, %29, %30, %31, %32, %33, %34, %35, %36, %37, %38, %39, %40, %41, %42, %43, %44, %45, %46, %47, %48, %49, %50, %51, %52, %53, %54, %55, %56, %57, %58, %59, %60, %61, %62, %63, %64, %65, %66, %67, %68, %69, %70, %71, %72, %73, %74, %75, %76, %77, %78, %79, %80, %81, %82, %83, %84, %85, %86, %87, %88, %89, %90, %91, %92, %93, %94, %95}, %96, %97, p, 1, 1, %99, %100;\n}\n"
        : "+f"(d[0]), "+f"(d[1]), "+f"(d[2]), "+f"(d[3]), "+f"(d[4]), "+f"(d[5]), "+f"(d[6]), "+f"(d[7]), "+f"(d[8]), "+f"(d[9]), "+f"(d[10]), "+f"(d[11]), "+f"(d[12]), "+f"(d[13]), "+f"(d[14]), "+f"(d[15]), "+f"(d[16]), "+f"(d[17]), "+f"(d[18]), "+f"(d[19]), "+f"(d[20]), "+f"(d[21]), "+f"(d[22]), "+f"(d[23]), "+f"(d[24]), "+f"(d[25]), "+f"(d[26]), "+f"(d[27]), "+f"(d[28]), "+f"(d[29]), "+f"(d[30]), "+f"(d[31]), "+f"(d[32]), "+f"(d[33]), "+f"(d[34]), "+f"(d[35]), "+f"(d[36]), "+f"(d[37]), "+f"(d[38]), "+f"(d[39]), "+f"(d[40]), "+f"(d[41]), "+f"(d[42]), "+f"(d[43]), "+f"(d[44]), "+f"(d[45]), "+f"(d[46]), "+f"(d[47]), "+f"(d[48]), "+f"(d[49]), "+f"(d[50]), "+f"(d[51]), "+f"(d[52]), "+f"(d[53]), "+f"(d[54]), "+f"(d[55]), "+f"(d[56]), "+f"(d[57]), "+f"(d[58]), "+f"(d[59]), "+f"(d[60]), "+f"(d[61]), "+f"(d[62]), "+f"(d[63]), "+f"(d[64]), "+f"(d[65]), "+f"(d[66]), "+f"(d[67]), "+f"(d[68]), "+f"(d[69]), "+f"(d[70]), "+f"(d[71]), "+f"(d[72]), "+f"(d[73]), "+f"(d[74]), "+f"(d[75]), "+f"(d[76]), "+f"(d[77]), "+f"(d[78]), "+f"(d[79]), "+f"(d[80]), "+f"(d[81]), "+f"(d[82]), "+f"(d[83]), "+f"(d[84]), "+f"(d[85]), "+f"(d[86]), "+f"(d[87]), "+f"(d[88]), "+f"(d[89]), "+f"(d[90]), "+f"(d[91]), "+f"(d[92]), "+f"(d[93]), "+f"(d[94]), "+f"(d[95])
        : "l"(da), "l"(db), "r"(scale_d), "n"(TA), "n"(TB));
}
template <int TA, int TB>
__device__ __forceinline__ void wgmma_n224(float (&d)[112], uint64_t da, uint64_t db, int scale_d) {
    asm volatile("{\n.reg .pred p;\nsetp.ne.b32 p, %114, 0;\n"
        "wgmma.mma_async.sync.aligned.m64n224k16.f32.bf16.bf16 {%0, %1, %2, %3, %4, %5, %6, %7, %8, %9, %10, %11, %12, %13, %14, %15, %16, %17, %18, %19, %20, %21, %22, %23, %24, %25, %26, %27, %28, %29, %30, %31, %32, %33, %34, %35, %36, %37, %38, %39, %40, %41, %42, %43, %44, %45, %46, %47, %48, %49, %50, %51, %52, %53, %54, %55, %56, %57, %58, %59, %60, %61, %62, %63, %64, %65, %66, %67, %68, %69, %70, %71, %72, %73, %74, %75, %76, %77, %78, %79, %80, %81, %82, %83, %84, %85, %86, %87, %88, %89, %90, %91, %92, %93, %94, %95, %96, %97, %98, %99, %100, %101, %102, %103, %104, %105, %106, %107, %108, %109, %110, %111}, %112, %113, p, 1, 1, %115, %116;\n}\n"
        : "+f"(d[0]), "+f"(d[1]), "+f"(d[2]), "+f"(d[3]), "+f"(d[4]), "+f"(d[5]), "+f"(d[6]), "+f"(d[7]), "+f"(d[8]), "+f"(d[9]), "+f"(d[10]), "+f"(d[11]), "+f"(d[12]), "+f"(d[13]), "+f"(d[14]), "+f"(d[15]), "+f"(d[16]), "+f"(d[17]), "+f"(d[18]), "+f"(d[19]), "+f"(d[20]), "+f"(d[21]), "+f"(d[22]), "+f"(d[23]), "+f"(d[24]), "+f"(d[25]), "+f"(d[26]), "+f"(d[27]), "+f"(d[28]), "+f"(d[29]), "+f"(d[30]), "+f"(d[31]), "+f"(d[32]), "+f"(d[33]), "+f"(d[34]), "+f"(d[35]), "+f"(d[36]), "+f"(d[37]), "+f"(d[38]), "+f"(d[39]), "+f"(d[40]), "+f"(d[41]), "+f"(d[42]), "+f"(d[43]), "+f"(d[44]), "+f"(d[45]), "+f"(d[46]), "+f"(d[47]), "+f"(d[48]), "+f"(d[49]), "+f"(d[50]), "+f"(d[51]), "+f"(d[52]), "+f"(d[53]), "+f"(d[54]), "+f"(d[55]), "+f"(d[56]), "+f"(d[57]), "+f"(d[58]), "+f"(d[59]), "+f"(d[60]), "+f"(d[61]), "+f"(d[62]), "+f"(d[63]), "+f"(d[64]), "+f"(d[65]), "+f"(d[66]), "+f"(d[67]), "+f"(d[68]), "+f"(d[69]), "+f"(d[70]), "+f"(d[71]), "+f"(d[72]), "+f"(d[73]), "+f"(d[74]), "+f"(d[75]), "+f"(d[76]), "+f"(d[77]), "+f"(d[78]), "+f"(d[79]), "+f"(d[80]), "+f"(d[81]), "+f"(d[82]), "+f"(d[83]), "+f"(d[84]), "+f"(d[85]), "+f"(d[86]), "+f"(d[87]), "+f"(d[88]), "+f"(d[89]), "+f"(d[90]), "+f"(d[91]), "+f"(d[92]), "+f"(d[93]), "+f"(d[94]), "+f"(d[95]), "+f"(d[96]), "+f"(d[97]), "+f"(d[98]), "+f"(d[99]), "+f"(d[100]), "+f"(d[101]), "+f"(d[102]), "+f"(d[103]), "+f"(d[104]), "+f"(d[105]), "+f"(d[106]), "+f"(d[107]), "+f"(d[108]), "+f"(d[109]), "+f"(d[110]), "+f"(d[111])
        : "l"(da), "l"(db), "r"(scale_d), "n"(TA), "n"(TB));
}
template <int TA, int TB>
__device__ __forceinline__ void wgmma_n256(float (&d)[128], uint64_t da, uint64_t db, int scale_d) {
    asm volatile("{\n.reg .pred p;\nsetp.ne.b32 p, %130, 0;\n"
        "wgmma.mma_async.sync.aligned.m64n256k16.f32.bf16.bf16 {%0, %1, %2, %3, %4, %5, %6, %7, %8, %9, %10, %11, %12, %13, %14, %15, %16, %17, %18, %19, %20, %21, %22, %23, %24, %25, %26, %27, %28, %29, %30, %31, %32, %33, %34, %35, %36, %37, %38, %39, %40, %41, %42, %43, %44, %45, %46, %47, %48, %49, %50, %51, %52, %53, %54, %55, %56, %57, %58, %59, %60, %61, %62, %63, %64, %65, %66, %67, %68, %69, %70, %71, %72, %73, %74, %75, %76, %77, %78, %79, %80, %81, %82, %83, %84, %85, %86, %87, %88, %89, %90, %91, %92, %93, %94, %95, %96, %97, %98, %99, %100, %101, %102, %103, %104, %105, %106, %107, %108, %109, %110, %111, %112, %113, %114, %115, %116, %117, %118, %119, %120, %121, %122, %123, %124, %125, %126, %127}, %128, %129, p, 1, 1, %131, %132;\n}\n"
        : "+f"(d[0]), "+f"(d[1]), "+f"(d[2]), "+f"(d[3]), "+f"(d[4]), "+f"(d[5]), "+f"(d[6]), "+f"(d[7]), "+f"(d[8]), "+f"(d[9]), "+f"(d[10]), "+f"(d[11]), "+f"(d[12]), "+f"(d[13]), "+f"(d[14]), "+f"(d[15]), "+f"(d[16]), "+f"(d[17]), "+f"(d[18]), "+f"(d[19]), "+f"(d[20]), "+f"(d[21]), "+f"(d[22]), "+f"(d[23]), "+f"(d[24]), "+f"(d[25]), "+f"(d[26]), "+f"(d[27]), "+f"(d[28]), "+f"(d[29]), "+f"(d[30]), "+f"(d[31]), "+f"(d[32]), "+f"(d[33]), "+f"(d[34]), "+f"(d[35]), "+f"(d[36]), "+f"(d[37]), "+f"(d[38]), "+f"(d[39]), "+f"(d[40]), "+f"(d[41]), "+f"(d[42]), "+f"(d[43]), "+f"(d[44]), "+f"(d[45]), "+f"(d[46]), "+f"(d[47]), "+f"(d[48]), "+f"(d[49]), "+f"(d[50]), "+f"(d[51]), "+f"(d[52]), "+f"(d[53]), "+f"(d[54]), "+f"(d[55]), "+f"(d[56]), "+f"(d[57]), "+f"(d[58]), "+f"(d[59]), "+f"(d[60]), "+f"(d[61]), "+f"(d[62]), "+f"(d[63]), "+f"(d[64]), "+f"(d[65]), "+f"(d[66]), "+f"(d[67]), "+f"(d[68]), "+f"(d[69]), "+f"(d[70]), "+f"(d[71]), "+f"(d[72]), "+f"(d[73]), "+f"(d[74]), "+f"(d[75]), "+f"(d[76]), "+f"(d[77]), "+f"(d[78]), "+f"(d[79]), "+f"(d[80]), "+f"(d[81]), "+f"(d[82]), "+f"(d[83]), "+f"(d[84]), "+f"(d[85]), "+f"(d[86]), "+f"(d[87]), "+f"(d[88]), "+f"(d[89]), "+f"(d[90]), "+f"(d[91]), "+f"(d[92]), "+f"(d[93]), "+f"(d[94]), "+f"(d[95]), "+f"(d[96]), "+f"(d[97]), "+f"(d[98]), "+f"(d[99]), "+f"(d[100]), "+f"(d[101]), "+f"(d[102]), "+f"(d[103]), "+f"(d[104]), "+f"(d[105]), "+f"(d[106]), "+f"(d[107]), "+f"(d[108]), "+f"(d[109]), "+f"(d[110]), "+f"(d[111]), "+f"(d[112]), "+f"(d[113]), "+f"(d[114]), "+f"(d[115]), "+f"(d[116]), "+f"(d[117]), "+f"(d[118]), "+f"(d[119]), "+f"(d[120]), "+f"(d[121]), "+f"(d[122]), "+f"(d[123]), "+f"(d[124]), "+f"(d[125]), "+f"(d[126]), "+f"(d[127])
        : "l"(da), "l"(db), "r"(scale_d), "n"(TA), "n"(TB));
}
template <int TA, int TB>
__device__ __forceinline__ void wgmma_n64(float (&d)[32], uint64_t da, uint64_t db, int scale_d) {
    asm volatile("{\n.reg .pred p;\nsetp.ne.b32 p, %34, 0;\n"
        "wgmma.mma_async.sync.aligned.m64n64k16.f32.bf16.bf16 {%0, %1, %2, %3, %4, %5, %6, %7, %8, %9, %10, %11, %12, %13, %14, %15, %16, %17, %18, %19, %20, %21, %22, %23, %24, %25, %26, %27, %28, %29, %30, %31}, %32, %33, p, 1, 1, %35, %36;\n}\n"
        : "+f"(d[0]), "+f"(d[1]), "+f"(d[2]), "+f"(d[3]), "+f"(d[4]), "+f"(d[5]), "+f"(d[6]), "+f"(d[7]), "+f"(d[8]), "+f"(d[9]), "+f"(d[10]), "+f"(d[11]), "+f"(d[12]), "+f"(d[13]), "+f"(d[14]), "+f"(d[15]), "+f"(d[16]), "+f"(d[17]), "+f"(d[18]), "+f"(d[19]), "+f"(d[20]), "+f"(d[21]), "+f"(d[22]), "+f"(d[23]), "+f"(d[24]), "+f"(d[25]), "+f"(d[26]), "+f"(d[27]), "+f"(d[28]), "+f"(d[29]), "+f"(d[30]), "+f"(d[31])
        : "l"(da), "l"(db), "r"(scale_d), "n"(TA), "n"(TB));
}
template <int TB>
__device__ __forceinline__ void wgmma_rs_n32(float (&d)[16], uint32_t a0, uint32_t a1, uint32_t a2, uint32_t a3, uint64_t db, int scale_d) {
    asm volatile("{\n.reg .pred p;\nsetp.ne.b32 p, %21, 0;\n"
        "wgmma.mma_async.sync.aligned.m64n32k16.f32.bf16.bf16 {%0, %1, %2, %3, %4, %5, %6, %7, %8, %9, %10, %11, %12, %13, %14, %15}, {%16, %17, %18, %19}, %20, p, 1, 1, %22;\n}\n"
        : "+f"(d[0]), "+f"(d[1]), "+f"(d[2]), "+f"(d[3]), "+f"(d[4]), "+f"(d[5]), "+f"(d[6]), "+f"(d[7]), "+f"(d[8]), "+f"(d[9]), "+f"(d[10]), "+f"(d[11]), "+f"(d[12]), "+f"(d[13]), "+f"(d[14]), "+f"(d[15])
        : "r"(a0), "r"(a1), "r"(a2), "r"(a3), "l"(db), "r"(scale_d), "n"(TB));
}
template <int TB>
__device__ __forceinline__ void wgmma_rs_n40(float (&d)[20], uint32_t a0, uint32_t a1, uint32_t a2, uint32_t a3, uint64_t db, int scale_d) {
    asm volatile("{\n.reg .pred p;\nsetp.ne.b32 p, %25, 0;\n"
        "wgmma.mma_async.sync.aligned.m64n40k16.f32.bf16.bf16 {%0, %1, %2, %3, %4, %5, %6, %7, %8, %9, %10, %11, %12, %13, %14, %15, %16, %17, %18, %19}, {%20, %21, %22, %23}, %24, p, 1, 1, %26;\n}\n"
        : "+f"(d[0]), "+f"(d[1]), "+f"(d[2]), "+f"(d[3]), "+f"(d[4]), "+f"(d[5]), "+f"(d[6]), "+f"(d[7]), "+f"(d[8]), "+f"(d[9]), "+f"(d[10]), "+f"(d[11]), "+f"(d[12]), "+f"(d[13]), "+f"(d[14]), "+f"(d[15]), "+f"(d[16]), "+f"(d[17]), "+f"(d[18]), "+f"(d[19])
        : "r"(a0), "r"(a1), "r"(a2), "r"(a3), "l"(db), "r"(scale_d), "n"(TB));
}

template <int V>
struct Int { static constexpr int value = V; };
struct Ring {
    uint32_t s, ph;
    __device__ __forceinline__ void next() {
        if (++s == NSTAGE) { s = 0; ph ^= 1; }
    }
};

template <int MODE, int NACC>
__device__ __forceinline__ void issue_stage(float (&acc)[NACC], const Ring& ring, uint32_t sbase, uint32_t bar_full, int wg) {
    const uint32_t slot = sbase + ring.s * SLOT;
    mbar_wait<0>(bar_full + 8 * ring.s, ring.ph);
    wgmma_fence();
#pragma unroll
    for (int j = 0; j < BK / 16; j++) {
        if constexpr (MODE == 0) {
            wgmma_n192<0, 1>(acc, mkdesc(slot + wg * (BK * 128) + j * 32, 16, BK * 16, BK == 64 ? 1 : 2), mkdesc(slot + BOFF + j * 2048, BK * 128, 1024, 1), 1);
        } else if constexpr (MODE == 1) {
            wgmma_n224<1, 1>(acc, mkdesc(slot + wg * (BK * 128) + j * 2048, BK * 128, 1024, 1), mkdesc(slot + BOFF + j * 1024, BK * 64, 512, 2), 1);
        } else {
            wgmma_n256<1, 1>(acc, mkdesc(slot + wg * (BK * 128) + j * 2048, BK * 128, 1024, 1), mkdesc(slot + BOFF + j * 2048, BK * 128, 1024, 1), 1);
        }
    }
    wgmma_commit();
}
template <int MODE, int NACC>
__device__ __forceinline__ void mainloop(float (&acc)[NACC], int nkb, Ring& ring, uint32_t sbase, uint32_t bar_full,
                                         uint32_t bar_empty, int wg, int lane) {
    uint32_t prev_s = 0;
#pragma unroll 1
    for (int kb = 0; kb < nkb; kb++) {
        issue_stage<MODE>(acc, ring, sbase, bar_full, wg);
        if (kb > 0) {
            wgmma_wait<1>();
            if (lane == 0) mbar_arrive(bar_empty + 8 * prev_s);
        }
        prev_s = ring.s;
        ring.next();
    }
    wgmma_wait<0>();
    if (lane == 0) mbar_arrive(bar_empty + 8 * prev_s);
}

template <int NC>
__device__ __forceinline__ void dual_softmax(const uint32_t (&pk)[NC][4], uint32_t (&P)[NC][4], uint32_t (&M)[NC][4]) {
    constexpr float L2E = 1.4426950408889634f;
    uint32_t mm[NC];
#pragma unroll
    for (int c = 0; c < NC; c++) {
        __nv_bfloat162 a0 = *(const __nv_bfloat162*)&pk[c][0], a1 = *(const __nv_bfloat162*)&pk[c][1];
        __nv_bfloat162 a2 = *(const __nv_bfloat162*)&pk[c][2], a3 = *(const __nv_bfloat162*)&pk[c][3];
        __nv_bfloat162 mx = __hmax2(__hmax2(a0, a1), __hmax2(a2, a3));
        __nv_bfloat162 mn = __hmin2(__hmin2(a0, a1), __hmin2(a2, a3));
        const uint32_t umx = *(const uint32_t*)&mx, umn = (*(const uint32_t*)&mn) ^ 0x80008000u;
        const uint32_t lo = __byte_perm(umx, umn, 0x5410), hi = __byte_perm(umx, umn, 0x7632);
        __nv_bfloat162 r = __hmax2(*(const __nv_bfloat162*)&lo, *(const __nv_bfloat162*)&hi);
        mm[c] = *(const uint32_t*)&r;
    }
#pragma unroll
    for (int o = 1; o <= 2; o <<= 1) {
        uint32_t t[NC];
#pragma unroll
        for (int c = 0; c < NC; c++) t[c] = __shfl_xor_sync(0xffffffffu, mm[c], o);
#pragma unroll
        for (int c = 0; c < NC; c++) {
            __nv_bfloat162 r = __hmax2(*(const __nv_bfloat162*)&mm[c], *(const __nv_bfloat162*)&t[c]);
            mm[c] = *(const uint32_t*)&r;
        }
    }
    float ep[NC][8], em[NC][8], sp[NC], sm[NC];
#pragma unroll
    for (int c = 0; c < NC; c++) {
        const float mxs = bf_lo(mm[c]) * L2E, mns = bf_hi(mm[c]) * L2E;
#pragma unroll
        for (int i = 0; i < 4; i++) {
            const float a = bf_lo(pk[c][i]), b = bf_hi(pk[c][i]);
            ep[c][2 * i] = ex2(fmaf(a, L2E, -mxs));
            ep[c][2 * i + 1] = ex2(fmaf(b, L2E, -mxs));
            em[c][2 * i] = ex2(fmaf(a, -L2E, -mns));
            em[c][2 * i + 1] = ex2(fmaf(b, -L2E, -mns));
        }
        sp[c] = ((ep[c][0] + ep[c][1]) + (ep[c][2] + ep[c][3])) + ((ep[c][4] + ep[c][5]) + (ep[c][6] + ep[c][7]));
        sm[c] = ((em[c][0] + em[c][1]) + (em[c][2] + em[c][3])) + ((em[c][4] + em[c][5]) + (em[c][6] + em[c][7]));
    }
#pragma unroll
    for (int o = 1; o <= 2; o <<= 1) {
        float tp[NC], tm[NC];
#pragma unroll
        for (int c = 0; c < NC; c++) {
            tp[c] = __shfl_xor_sync(0xffffffffu, sp[c], o);
            tm[c] = __shfl_xor_sync(0xffffffffu, sm[c], o);
        }
#pragma unroll
        for (int c = 0; c < NC; c++) { sp[c] += tp[c]; sm[c] += tm[c]; }
    }
#pragma unroll
    for (int c = 0; c < NC; c++) {
        const float rp = rcp_fast(sp[c]), rm = rcp_fast(sm[c]);
#pragma unroll
        for (int i = 0; i < 4; i++) {
            P[c][i] = pack2(ep[c][2 * i] * rp, ep[c][2 * i + 1] * rp);
            M[c][i] = pack2(em[c][2 * i] * rm, em[c][2 * i + 1] * rm);
        }
    }
}

template <int NR>
__device__ __forceinline__ void ln_rows(const __nv_bfloat16* x, const __nv_bfloat16* gate_w, int row0, int row_end, int lane) {
    uint4 v[NR][4];
    float sh[NR], red[NR][3];
#pragma unroll
    for (int h = 0; h < NR; h++) {
        const int row = min(row0 + h, row_end - 1);
#pragma unroll
        for (int c = 0; c < 4; c++) v[h][c] = __ldg((const uint4*)(x + (size_t)row * D_) + c * 32 + lane);
        sh[h] = __bfloat162float(__ldg(x + (size_t)row * D_));
        red[h][0] = red[h][1] = red[h][2] = 0.f;
    }
#pragma unroll
    for (int c = 0; c < 4; c++) {
        const uint4 gw = __ldg((const uint4*)gate_w + c * 32 + lane);
        const uint32_t q[4] = {gw.x, gw.y, gw.z, gw.w};
#pragma unroll
        for (int h = 0; h < NR; h++) {
            const uint32_t w[4] = {v[h][c].x, v[h][c].y, v[h][c].z, v[h][c].w};
            float s0 = 0.f, q0 = 0.f, d0 = 0.f;
#pragma unroll
            for (int k = 0; k < 4; k++) {
                const float a = bf_lo(w[k]) - sh[h], b = bf_hi(w[k]) - sh[h];
                s0 += a + b;
                q0 = fmaf(a, a, fmaf(b, b, q0));
                d0 = fmaf(bf_lo(w[k]), bf_lo(q[k]), fmaf(bf_hi(w[k]), bf_hi(q[k]), d0));
            }
            red[h][0] += s0; red[h][1] += q0; red[h][2] += d0;
        }
    }
#pragma unroll
    for (int o = 16; o > 0; o >>= 1) {
        float t[NR][3];
#pragma unroll
        for (int h = 0; h < NR; h++)
#pragma unroll
            for (int k = 0; k < 3; k++) t[h][k] = __shfl_xor_sync(0xffffffffu, red[h][k], o);
#pragma unroll
        for (int h = 0; h < NR; h++)
#pragma unroll
            for (int k = 0; k < 3; k++) red[h][k] += t[h][k];
    }
#pragma unroll
    for (int h = 0; h < NR; h++) {
        if (row0 + h < row_end) {
            const float ms = red[h][0] * (1.f / D_);
            const float var = fmaxf(red[h][1] * (1.f / D_) - ms * ms, 0.f);
            const float rstd = rsqrtf(var + 1e-5f);
            const float nm = -(ms + sh[h]) * rstd;
            uint4* hr = (uint4*)(g_h + (size_t)(row0 + h) * D_) + lane;
#pragma unroll
            for (int c = 0; c < 4; c++) {
                uint4 o;
                o.x = pack2(fmaf(bf_lo(v[h][c].x), rstd, nm), fmaf(bf_hi(v[h][c].x), rstd, nm));
                o.y = pack2(fmaf(bf_lo(v[h][c].y), rstd, nm), fmaf(bf_hi(v[h][c].y), rstd, nm));
                o.z = pack2(fmaf(bf_lo(v[h][c].z), rstd, nm), fmaf(bf_hi(v[h][c].z), rstd, nm));
                o.w = pack2(fmaf(bf_lo(v[h][c].w), rstd, nm), fmaf(bf_hi(v[h][c].w), rstd, nm));
                hr[c * 32] = o;
            }
            if (lane == 0) g_gate[row0 + h] = 1.f / (1.f + __expf(-red[h][2]));
        }
    }
}

struct Params {
    const __nv_bfloat16* x;
    const __nv_bfloat16* wphi;
    const __nv_bfloat16* b1;
    const __nv_bfloat16* b2;
    const __nv_bfloat16* gate_w;
};

__global__ void __launch_bounds__(NTHREADS, 1)
fused_kernel(const __grid_constant__ CUtensorMap m_x, const __grid_constant__ CUtensorMap m_wqkv,
             const __grid_constant__ CUtensorMap m_h, const __grid_constant__ CUtensorMap m_w1,
             const __grid_constant__ CUtensorMap m_w2, const __grid_constant__ CUtensorMap m_u,
             const __grid_constant__ CUtensorMap m_o, const __grid_constant__ CUtensorMap m_wo,
             const __grid_constant__ CUtensorMap m_os, const __grid_constant__ CUtensorMap m_out, const Params prm) {
    extern __shared__ uint8_t smem_raw[];
    const uint32_t sbase = (smem_u32(smem_raw) + 1023u) & ~1023u;
    const uint32_t bar_full = sbase + OFF_BAR;
    const uint32_t bar_empty = bar_full + 8 * NSTAGE;
    const uint32_t bar_stg_full = bar_empty + 8 * NSTAGE;
    const uint32_t bar_stg_empty = bar_stg_full + 8;
    const uint32_t bar_w = bar_stg_empty + 8;
    const uint32_t bar_phi = bar_w + 8;
    const uint32_t bar_kvd = bar_phi + 8;
    const uint32_t bar_kvx = bar_kvd + 8;
    const uint32_t bar_od = bar_kvx + 8;
    const uint32_t stg = sbase + OFF_STG;

    const int tid = threadIdx.x;
    const int warp = __shfl_sync(0xffffffffu, tid >> 5, 0), lane = tid & 31;
    const int cta = blockIdx.x;
    const int r = cta & 1, p = cta >> 1;
    const int hp = p & 15, tg = p >> 4;
    const int tok_a = tg * 4 + r, tok_b = tg * 4 + 2 + r;
    const int ft = p & 15, dt = (p >> 4) * 2 + r;
    const int st = (p & 7) * 2 + r, nt = (p >> 3) & 3, kh = p >> 5;
    const bool ts0 = tg == 0 && r == 0;
    const int nB = kh ? FB - N0 : N0;
    const int l7 = lane & 7, lb3 = (lane >> 3) & 1, lb4 = lane >> 4;
    const unsigned epoch = ld_relaxed(&g_flags[FL_LN * 32]) / NCTA;

    if (tid == 32) {
        asm volatile("prefetch.tensormap [%0];" ::"l"((uint64_t)&m_x) : "memory");
        asm volatile("prefetch.tensormap [%0];" ::"l"((uint64_t)&m_wqkv) : "memory");
        asm volatile("prefetch.tensormap [%0];" ::"l"((uint64_t)&m_h) : "memory");
        asm volatile("prefetch.tensormap [%0];" ::"l"((uint64_t)&m_w1) : "memory");
    }
    if (tid == 256) {
        for (int i = 0; i < NSTAGE; i++) {
            mbar_init(bar_full + 8 * i, 1);
            mbar_init(bar_empty + 8 * i, 8);
        }
        mbar_init(bar_stg_full, 8);
        mbar_init(bar_stg_empty, 1);
        mbar_init(bar_w, 1);
        mbar_init(bar_phi, 1);
        mbar_init(bar_kvd, 8);
        mbar_init(bar_kvx, 1);
        mbar_init(bar_od, 8);
        fence_async_smem();
#pragma unroll 1
        for (int i = 0; i < NSTAGE; i++) {
            mbar_expect_tx(bar_full + 8 * i, BK * 640);
            tma3d(sbase + i * SLOT, &m_x, i * BK, tok_a * 128, 0, bar_full + 8 * i);
            tma3d(sbase + i * SLOT + BOFF, &m_wqkv, hp * 64, i * BK, 0, bar_full + 8 * i);
        }
    }
    __syncthreads();

    if (warp >= 8) {
      asm volatile("setmaxnreg.dec.sync.aligned.u32 120;");
      if (warp == 8) {
        {
            uint32_t fb = bar_full, dst = sbase, par = 0;
            auto phase = [&](const CUtensorMap* ma, int a1, int a2, bool a_on_0, const CUtensorMap* mb, int b0, int b2, int k0, uint32_t bytes, int cnt) {
#pragma unroll 1
                for (int i = 0; i < cnt; i++) {
                    mbar_wait<2>(fb + 8 * NSTAGE, par);
                    if (elect_one()) {
                        mbar_expect_tx(fb, bytes);
                        tma3d(dst, ma, a_on_0 ? k0 : 0, a_on_0 ? a1 : k0, a2, fb);
                        tma3d(dst + BOFF, mb, b0, k0, b2, fb);
                    }
                    k0 += BK;
                    fb += 8; dst += SLOT;
                    if (fb == bar_full + 8 * NSTAGE) { fb = bar_full; dst = sbase; par ^= 1; }
                }
            };
            auto dep = [&](int flag, unsigned target, int tl) {
                (void)tl;
                wait_flag<2>(&g_flags[flag * 32], target, epoch);
                fence_async_glob();
            };
            phase(&m_x, tok_a * 128, 0, true, &m_wqkv, hp * 64, 0, NSTAGE * BK, BK * 640, 1024 / BK - NSTAGE);
            dep(FL_LN, NCTA, 20);
            phase(&m_h, 0, dt * 2, false, &m_w1, 0, ft * 7, 0, BK * 704, 768 / BK);
            dep(FL_LN1, NCTA, 26);
            phase(&m_h, 0, dt * 2, false, &m_w1, 0, ft * 7, 768, BK * 704, 768 / BK);
            dep(FL_LN2, NCTA, 26);
            phase(&m_h, 0, dt * 2, false, &m_w1, 0, ft * 7, 1536, BK * 704, 512 / BK);
            phase(&m_x, tok_b * 128, 0, true, &m_wqkv, hp * 64, 0, 0, BK * 640, 1024 / BK);
            static_assert(N0 * BK == 8 * 224, "K halves start at an f-tile boundary");
            dep(FL_UF + nt * 2 + kh, 2, 22);
            phase(&m_w2, 0, st * 2, false, &m_u, 0, nt * 4, kh ? N0 * BK : 0, BK * 768, 192 / BK);
            dep(FL_U + nt, 32, 28);
            phase(&m_w2, 0, st * 2, false, &m_u, 0, nt * 4, (kh ? N0 * BK : 0) + 192, BK * 768, nB - 192 / BK);
            dep(FL_O + st * 2 + kh, 8, 24);
            phase(&m_o, 0, st * 2, false, &m_wo, 0, nt * 4, kh ? 512 : 0, BK * 768, 512 / BK);
        }
      } else {
        const int et = tid - 288, sw = warp - 9;
        const int g8 = lane >> 2, t4 = lane & 3;
        {
            if (ts0) {
#pragma unroll
                for (int i = 0; i < 16; i++) g_kvsum[(hp * 16 + i) * 96 + et] = make_float4(0.f, 0.f, 0.f, 0.f);
            }
#pragma unroll 1
            for (int b = 0; b < 3; b++) {
                const int row0 = b * 768 + cta * (b < 2 ? 6 : 4) + sw * 2;
                if (b < 2 || sw < 2) ln_rows<2>(prm.x, prm.gate_w, row0, row0 + 2, lane);
                if (b == 0) {
                    for (int idx = et; idx < 256; idx += 96) {
                        const int k = (idx >> 2) & 31, u = idx & 3, h = idx >> 7;
                        sts128(sbase + OFF_WPHI + h * 4096 + k * 128 + ((u ^ (k & 7)) << 4),
                               __ldg((const uint4*)(prm.wphi + ((size_t)(hp * 2 + h) * 32 + k) * 32 + u * 8)));
                    }
                    fence_async_smem();
                }
                fence_async_glob();
                bar_sync(1, 96);
                if (et == 0) {
                    if (b == 0) mbar_arrive(bar_w);
                    flag_add(&g_flags[(b == 0 ? FL_LN : b == 1 ? FL_LN1 : FL_LN2) * 32]);
                }
            }
        }

#pragma unroll 1
        for (int tile = 0; tile < 2; tile++) {
            if (tile) {
                mbar_wait<1>(bar_stg_full, 1);
#pragma unroll 1
                for (int idx = et; idx < 896; idx += 96) {
                    uint4 a[4];
                    __nv_bfloat162 b[4];
                    const int u = idx & 15;
#pragma unroll
                    for (int h = 0; h < 4; h++) {
                        const int row = (idx >> 4) + h * 56;
                        a[h] = lds128(stg + row * 256 + ((u ^ (row & 7)) << 4));
                        b[h] = __bfloat162bfloat162(__ldg(prm.b1 + ft * 224 + row));
                    }
#pragma unroll
                    for (int h = 0; h < 4; h++) {
                        const int row = (idx >> 4) + h * 56;
                        const uint32_t av[4] = {a[h].x, a[h].y, a[h].z, a[h].w};
                        uint32_t ov[4];
#pragma unroll
                        for (int k = 0; k < 4; k++) {
                            const __nv_bfloat162 ts2 = __hadd2(*(const __nv_bfloat162*)&av[k], b[h]);
                            const uint32_t tsum = *(const uint32_t*)&ts2;
                            ov[k] = h < GH ? av[k] : pack2(gelu_tanh(bf_lo(tsum)), gelu_tanh(bf_hi(tsum)));
                        }
                        *(uint4*)(g_u + (size_t)(ft * 224 + row) * D_ + dt * 128 + u * 8) = make_uint4(ov[0], ov[1], ov[2], ov[3]);
                    }
                }
                fence_async_glob();
                bar_sync(1, 96);
                if (et == 0) {
                    mbar_arrive(bar_stg_empty);
                    flag_add(&g_flags[(FL_U + (dt >> 1)) * 32]);
                    if ((ft & 7) == 0) asm volatile("red.relaxed.gpu.global.add.u32 [%0], 1;" ::"l"(&g_flags[(FL_UF + (dt >> 1) * 2 + (ft >> 3)) * 32]) : "memory");
                }
            }
            mbar_wait<1>(bar_stg_full, 0);
            for (int idx = et; idx < 256; idx += 96)
                sts128(stg + 32768 + idx * 128 + ((4 ^ (idx & 7)) << 4), make_uint4(0x3F803F80u, 0x3F803F80u, 0x3F803F80u, 0x3F803F80u));
#pragma unroll 1
            for (int it = sw * 2; it < 16; it += (it & 1) ? 5 : 1) {
                const int rb = it >> 1, which = it & 1;
                const uint32_t rowa = stg + (rb * 16 + l7 + lb3 * 8) * 128;
                uint32_t pk[4][4], P[4][4], M[4][4];
#pragma unroll
                for (int j = 0; j < 4; j++)
                    ldsm4(rowa + which * 16384 + (((j * 2 + lb4) ^ l7) << 4), pk[(j >> 1) * 2][(j & 1) * 2], pk[(j >> 1) * 2 + 1][(j & 1) * 2],
                          pk[(j >> 1) * 2][(j & 1) * 2 + 1], pk[(j >> 1) * 2 + 1][(j & 1) * 2 + 1]);
                dual_softmax<4>(pk, P, M);
                if (which == 0) {
                    uint4* dst = &g_pq[(size_t)((cta * 16 + tile * 8 + rb) * 8) * 32 + lane];
#pragma unroll
                    for (int hh = 0; hh < 2; hh++) {
                        dst[(hh * 4 + 0) * 32] = make_uint4(P[2 * hh][0], P[2 * hh + 1][0], P[2 * hh][1], P[2 * hh + 1][1]);
                        dst[(hh * 4 + 1) * 32] = make_uint4(P[2 * hh][2], P[2 * hh + 1][2], P[2 * hh][3], P[2 * hh + 1][3]);
                        dst[(hh * 4 + 2) * 32] = make_uint4(M[2 * hh][0], M[2 * hh + 1][0], M[2 * hh][1], M[2 * hh + 1][1]);
                        dst[(hh * 4 + 3) * 32] = make_uint4(M[2 * hh][2], M[2 * hh + 1][2], M[2 * hh][3], M[2 * hh + 1][3]);
                    }
                } else {
#pragma unroll
                    for (int hh = 0; hh < 2; hh++) {
                        const uint32_t base = rowa + hh * 16384;
                        stmatrix4(base + (((0 + lb4) ^ l7) << 4), P[2 * hh][0], P[2 * hh + 1][0], P[2 * hh][1], P[2 * hh + 1][1]);
                        stmatrix4(base + (((2 + lb4) ^ l7) << 4), P[2 * hh][2], P[2 * hh + 1][2], P[2 * hh][3], P[2 * hh + 1][3]);
                        stmatrix4(base + (((4 + lb4) ^ l7) << 4), M[2 * hh][0], M[2 * hh + 1][0], M[2 * hh][1], M[2 * hh + 1][1]);
                        stmatrix4(base + (((6 + lb4) ^ l7) << 4), M[2 * hh][2], M[2 * hh + 1][2], M[2 * hh][3], M[2 * hh + 1][3]);
                    }
                }
            }
            fence_async_smem();
            if (tile == 0 && et == 0) wait_flag<1>(&g_flags[FL_LN * 32], NCTA, epoch);
            bar_sync(1, 96);
            if (et == 0) mbar_arrive(bar_phi);
        }
        if (et == 0) {
            mbar_wait<1>(bar_kvd, 1);
            flag_add(&g_flags[(FL_KV + hp) * 32]);
            wait_flag<1>(&g_flags[(FL_KV + hp) * 32], 8, epoch);
        }
        bar_sync(1, 96);
#pragma unroll
        for (int hh = 0; hh < 2; hh++) {
            float4 sv[8];
#pragma unroll
            for (int i = 0; i < 8; i++) sv[i] = __ldcg(&g_kvsum[((hp * 2 + hh) * 8 + i) * 96 + et]);
            const uint32_t base = stg + 32768 + hh * 8192 + (sw * 16 + g8) * 128 + t4 * 4;
#pragma unroll
            for (int i = 0; i < 8; i++) {
                sts32(base + ((i ^ g8) << 4), pack2(sv[i].x, sv[i].y));
                if (sw < 2) sts32(base + 1024 + ((i ^ g8) << 4), pack2(sv[i].z, sv[i].w));
            }
        }
        fence_async_smem();
        bar_sync(1, 96);
        if (et == 0) {
            mbar_arrive(bar_kvx);
            mbar_wait<1>(bar_od, 0);
            tma3d_store(&m_os, stg, 0, hp * 64, tok_a * 2);
            tma3d_store(&m_os, stg + 16384, 0, hp * 64, tok_b * 2);
            bulk_commit();
            bulk_wait_all();
            fence_async_glob();
            asm volatile("red.relaxed.gpu.global.add.u32 [%0], 1;" ::"l"(&g_flags[(FL_O + tok_a * 2 + (hp >> 3)) * 32]) : "memory");
            asm volatile("red.relaxed.gpu.global.add.u32 [%0], 1;" ::"l"(&g_flags[(FL_O + tok_b * 2 + (hp >> 3)) * 32]) : "memory");
        }
      }
    } else {
        asm volatile("setmaxnreg.inc.sync.aligned.u32 192;");
        const int wg = warp >> 2, wq = warp & 3;
        const int mrow = wg * 64 + wq * 16 + lb3 * 8 + l7;
        Ring ring{0, 0};
        auto kv_section = [&](uint32_t parity, auto mode, auto& acc) {
            mbar_wait<0>(bar_phi, parity);
            float c[32];
            zero(c);
            pin(c);
            wgmma_fence();
#pragma unroll
            for (int ks = 0; ks < 8; ks++)
                wgmma_n64<1, 1>(c, mkdesc(stg + 32768 + wg * 16384 + ks * 2048, 8192, 1024, 1), mkdesc(stg + wg * 16384 + ks * 2048, 8192, 1024, 1), 1);
            wgmma_commit();
            issue_stage<decltype(mode)::value>(acc, ring, sbase, bar_full, wg);
            const uint32_t s_a = ring.s;
            ring.next();
            issue_stage<decltype(mode)::value>(acc, ring, sbase, bar_full, wg);
            const uint32_t s_b = ring.s;
            ring.next();
            wgmma_wait<2>();
            pin(c);
            if (wq < 3) {
#pragma unroll
                for (int i = 0; i < 8; i++)
                    red_add4(&g_kvsum[((hp * 2 + wg) * 8 + i) * 96 + wq * 32 + lane],
                             make_float4(c[4 * i], c[4 * i + 1], wq == 2 ? 0.f : c[4 * i + 2], wq == 2 ? 0.f : c[4 * i + 3]));
            }
            __syncwarp();
            if (lane == 0) mbar_arrive(bar_kvd);
            wgmma_wait<0>();
            if (lane == 0) { mbar_arrive(bar_empty + 8 * s_a); mbar_arrive(bar_empty + 8 * s_b); }
        };

#pragma unroll 1
        for (int pass = 0; pass < 2; pass++) {
            {
                float acc[96];
                zero(acc);
                mainloop<0>(acc, 1024 / BK, ring, sbase, bar_full, bar_empty, wg, lane);
                mbar_wait<0>(pass ? bar_stg_empty : bar_w, 0);
                float pf[4][16];
                {
                    uint32_t a[8][4];
#pragma unroll
                    for (int j = 0; j < 8; j++) {
                        a[j][0] = pack2(acc[8 * j], acc[8 * j + 1]); a[j][1] = pack2(acc[8 * j + 2], acc[8 * j + 3]);
                        a[j][2] = pack2(acc[8 * j + 4], acc[8 * j + 5]); a[j][3] = pack2(acc[8 * j + 6], acc[8 * j + 7]);
                    }
                    zero(pf[0]); zero(pf[1]); zero(pf[2]); zero(pf[3]);
                    pin(pf[0]); pin(pf[1]); pin(pf[2]); pin(pf[3]);
#pragma unroll
                    for (int j = 0; j < 8; j++) { pin(a[j][0]); pin(a[j][1]); pin(a[j][2]); pin(a[j][3]); }
                    wgmma_fence();
#pragma unroll
                    for (int j = 0; j < 8; j++)
                        wgmma_rs_n32<1>(pf[j >> 1], a[j][0], a[j][1], a[j][2], a[j][3], mkdesc(sbase + OFF_WPHI + (j & 3) * 2048, 4096, 1024, 1), 1);
                    wgmma_commit();
                }
                const uint32_t base = stg + mrow * 128;
#pragma unroll
                for (int j = 0; j < 4; j++)
                    stmatrix4(base + 32768 + (j >> 1) * 16384 + ((((j & 1) * 2 + lb4) ^ l7) << 4),
                              pack2(acc[64 + 8 * j], acc[65 + 8 * j]), pack2(acc[66 + 8 * j], acc[67 + 8 * j]),
                              pack2(acc[68 + 8 * j], acc[69 + 8 * j]), pack2(acc[70 + 8 * j], acc[71 + 8 * j]));
                wgmma_wait<0>();
#pragma unroll
                for (int j = 0; j < 8; j++) {
                    const float* f = &pf[j >> 1][(j & 1) * 8];
                    stmatrix4(base + (j >> 2) * 16384 + ((((j & 3) * 2 + lb4) ^ l7) << 4),
                              pack2(f[0], f[1]), pack2(f[2], f[3]), pack2(f[4], f[5]), pack2(f[6], f[7]));
                }
                fence_async_smem();
                __syncwarp();
                if (lane == 0) mbar_arrive(bar_stg_full);
            }
            if (pass == 0) {
                float acc[112];
                zero(acc);
#pragma unroll 1
                for (int half = 0; half < 2; half++) {
                    mainloop<1>(acc, half ? (2048 - KVA) / BK - 2 : KVA / BK, ring, sbase, bar_full, bar_empty, wg, lane);
                    if (half == 0) kv_section(0, Int<1>(), acc);
                }
                mbar_wait<0>(bar_kvd, 0);
                const uint32_t base = stg + (lb4 * 8 + l7) * 256 + (((wg * 8 + wq * 2 + lb3) ^ l7) << 4);
                uint32_t pk[56];
#pragma unroll
                for (int i = 0; i < 56; i++) pk[i] = pack2(acc[2 * i], acc[2 * i + 1]);
#pragma unroll
                for (int b = 0; b < 7 * GH; b++) {
                    const __nv_bfloat162 bb = __ldg((const __nv_bfloat162*)(prm.b1 + ft * 224 + b * 8 + (lane & 3) * 2));
#pragma unroll
                    for (int h = 0; h < 2; h++) {
                        const __nv_bfloat162 t2 = __hadd2(*(const __nv_bfloat162*)&pk[2 * b + h], bb);
                        const uint32_t t = *(const uint32_t*)&t2;
                        pk[2 * b + h] = pack2(gelu_tanh(bf_lo(t)), gelu_tanh(bf_hi(t)));
                    }
                }
#pragma unroll
                for (int jb = 0; jb < 14; jb++) stmatrix4t(base + jb * 4096, pk[4 * jb], pk[4 * jb + 1], pk[4 * jb + 2], pk[4 * jb + 3]);
                __syncwarp();
                if (lane == 0) mbar_arrive(bar_stg_full);
            }
        }
        float acc[128];
        zero(acc);
        const int grow = st * 128 + wg * 64 + wq * 16 + (lane >> 2);
        mainloop<2>(acc, S1, ring, sbase, bar_full, bar_empty, wg, lane);
        kv_section(1, Int<2>(), acc);
        mainloop<2>(acc, S2 - S1 - 2, ring, sbase, bar_full, bar_empty, wg, lane);
        {
            const uint4* src = &g_pq[(size_t)((cta * 16 + wg * 8 + wq) * 8) * 32 + lane];
            const int orow = (wg ? tok_b : tok_a) * 128 + wq * 16 + (lane >> 2);
            uint4 qn[4];
#pragma unroll
            for (int i = 0; i < 4; i++) qn[i] = __ldcg(src + i * 32);
            const float ga0 = __ldcg(&g_gate[orow]), ga1 = __ldcg(&g_gate[orow + 8]);
            const float gb0 = __ldcg(&g_gate[orow + 64]), gb1 = __ldcg(&g_gate[orow + 72]);
            mbar_wait<0>(bar_kvx, 0);
            uint32_t op0 = 0, op1 = 0;
#pragma unroll 1
            for (int un = 0; un < 4; un++) {
                const int mb = un >> 1, hh = un & 1;
                uint4 q[4];
#pragma unroll
                for (int i = 0; i < 4; i++) q[i] = qn[i];
                if (un < 3) {
                    const uint4* nsrc = src + (((un + 1) >> 1) * 32 + ((un + 1) & 1) * 4) * 32;
#pragma unroll
                    for (int i = 0; i < 4; i++) qn[i] = __ldcg(nsrc + i * 32);
                }
                const float gt0 = mb ? gb0 : ga0, gt1 = mb ? gb1 : ga1;
                float o[20];
                zero(o);
                pin(o);
#pragma unroll
                for (int i = 0; i < 4; i++) { pin(q[i].x); pin(q[i].y); pin(q[i].z); pin(q[i].w); }
                wgmma_fence();
#pragma unroll
                for (int j = 0; j < 4; j++)
                    wgmma_rs_n40<0>(o, q[j].x, q[j].y, q[j].z, q[j].w, mkdesc(stg + 32768 + hh * 8192 + j * 32, 16, 1024, 1), 1);
                wgmma_commit();
                issue_stage<2>(acc, ring, sbase, bar_full, wg);
                const uint32_t s_a = ring.s;
                ring.next();
                issue_stage<2>(acc, ring, sbase, bar_full, wg);
                wgmma_wait<2>();
                if (un > 0 && lane == 0) { mbar_arrive(bar_empty + 8 * op0); mbar_arrive(bar_empty + 8 * op1); }
                op0 = s_a; op1 = ring.s;
                ring.next();
                pin(o);
#pragma unroll
                for (int i = 0; i < 4; i++) { pin(q[i].x); pin(q[i].y); pin(q[i].z); pin(q[i].w); }
                const float s0 = gt0 * rcp_fast(o[16] + 1e-6f), s1 = gt1 * rcp_fast(o[18] + 1e-6f);
                const uint32_t base = stg + wg * 16384 + mb * 8192 + (hh * 32 + lb4 * 8 + l7) * 128 + (((wq * 2 + lb3) ^ l7) << 4);
                stmatrix4t(base, pack2(o[0] * s0, o[1] * s0), pack2(o[2] * s1, o[3] * s1),
                           pack2(o[4] * s0, o[5] * s0), pack2(o[6] * s1, o[7] * s1));
                stmatrix4t(base + 2048, pack2(o[8] * s0, o[9] * s0), pack2(o[10] * s1, o[11] * s1),
                           pack2(o[12] * s0, o[13] * s0), pack2(o[14] * s1, o[15] * s1));
            }
            fence_async_smem();
            __syncwarp();
            if (lane == 0) mbar_arrive(bar_od);
            wgmma_wait<0>();
            if (lane == 0) { mbar_arrive(bar_empty + 8 * op0); mbar_arrive(bar_empty + 8 * op1); }
        }
        mainloop<2>(acc, nB - S2 - 8, ring, sbase, bar_full, bar_empty, wg, lane);
        {
            const float c0 = 1.f - __ldcg(&g_gate[grow]), c1 = 1.f - __ldcg(&g_gate[grow + 8]);
            const float b0 = kh ? __bfloat162float(prm.b2[grow]) : 0.f, b1v = kh ? __bfloat162float(prm.b2[grow + 8]) : 0.f;
#pragma unroll
            for (int i = 0; i < 32; i++) {
                acc[4 * i] = (acc[4 * i] + b0) * c0;
                acc[4 * i + 1] = (acc[4 * i + 1] + b0) * c0;
                acc[4 * i + 2] = (acc[4 * i + 2] + b1v) * c1;
                acc[4 * i + 3] = (acc[4 * i + 3] + b1v) * c1;
            }
        }
        mainloop<2>(acc, 512 / BK, ring, sbase, bar_full, bar_empty, wg, lane);
        {
            const int tile = st * 4 + nt;
            uint4* dst = &g_part[(size_t)(tile * 2 + kh) * 8 * 256 + tid];
#pragma unroll
            for (int i = 0; i < 8; i++) {
                uint32_t v[4];
#pragma unroll
                for (int k = 0; k < 4; k++)
                    v[k] = kh ? pack2(acc[8 * i + 2 * k], acc[8 * i + 2 * k + 1]) : pack2(acc[64 + 8 * i + 2 * k], acc[65 + 8 * i + 2 * k]);
                dst[i * 256] = make_uint4(v[0], v[1], v[2], v[3]);
            }
            bar_sync(2, 256);
            if (tid == 0) {
                flag_add(&g_flags[(FL_PART + tile * 2 + kh) * 32]);
                wait_flag<0>(&g_flags[(FL_PART + tile * 2 + (kh ^ 1)) * 32], 1, epoch);
            }
            bar_sync(2, 256);
            const uint4* src = &g_part[(size_t)(tile * 2 + (kh ^ 1)) * 8 * 256 + tid];
            uint4 pv[8];
#pragma unroll
            for (int i = 0; i < 8; i++) pv[i] = __ldcg(src + i * 256);
            const uint32_t obase = sbase + wg * 16384 + (wq * 16 + lb3 * 8 + l7) * 128;
#pragma unroll
            for (int i = 0; i < 8; i++) {
                float f[8];
#pragma unroll
                for (int k = 0; k < 8; k++) f[k] = kh ? acc[64 + 8 * i + k] : acc[8 * i + k];
                stmatrix4(obase + (i >> 2) * 8192 + (((((2 * i) & 7) + lb4) ^ l7) << 4),
                          pack2(f[0] + bf_lo(pv[i].x), f[1] + bf_hi(pv[i].x)), pack2(f[2] + bf_lo(pv[i].y), f[3] + bf_hi(pv[i].y)),
                          pack2(f[4] + bf_lo(pv[i].z), f[5] + bf_hi(pv[i].z)), pack2(f[6] + bf_lo(pv[i].w), f[7] + bf_hi(pv[i].w)));
            }
            fence_async_smem();
            bar_sync(3 + wg, 128);
            if ((tid & 127) == 0) {
#pragma unroll
                for (int c = 0; c < 2; c++)
                    tma2d_store(&m_out, sbase + wg * 16384 + c * 8192, nt * 256 + kh * 128 + c * 64, st * 128 + wg * 64);
                bulk_commit();
                bulk_wait_read();
            }
        }
    }
}

typedef CUresult (*EncodeFn)(CUtensorMap*, CUtensorMapDataType, cuuint32_t, void*, const cuuint64_t*, const cuuint64_t*,
                             const cuuint32_t*, const cuuint32_t*, CUtensorMapInterleave, CUtensorMapSwizzle,
                             CUtensorMapL2promotion, CUtensorMapFloatOOBfill);

void make_map(EncodeFn enc, CUtensorMap* m, const void* ptr, int rank, const uint64_t* dims, const uint64_t* strides_bytes,
              const uint32_t* box, CUtensorMapSwizzle swz) {
    cuuint64_t gd[3], gs[2];
    cuuint32_t bd[3], es[3] = {1, 1, 1};
    for (int i = 0; i < rank; i++) { gd[i] = dims[i]; bd[i] = box[i]; }
    for (int i = 0; i < rank - 1; i++) gs[i] = strides_bytes[i];
    CUresult res = enc(m, CU_TENSOR_MAP_DATA_TYPE_BFLOAT16, rank, const_cast<void*>(ptr), gd, gs, bd, es, CU_TENSOR_MAP_INTERLEAVE_NONE, swz,
        CU_TENSOR_MAP_L2_PROMOTION_L2_128B, CU_TENSOR_MAP_FLOAT_OOB_FILL_NONE);
    (void)res;
}

}

extern "C" void kernel_launch(void* const* d_in, const int* in_sizes, int n_in, void* d_out, int out_size) {
    (void)in_sizes; (void)n_in; (void)out_size;
    const __nv_bfloat16* x = (const __nv_bfloat16*)d_in[0];
    const __nv_bfloat16* wqkv = (const __nv_bfloat16*)d_in[1];
    const __nv_bfloat16* wphi = (const __nv_bfloat16*)d_in[2];
    const __nv_bfloat16* wo = (const __nv_bfloat16*)d_in[3];
    const __nv_bfloat16* w1 = (const __nv_bfloat16*)d_in[5];
    const __nv_bfloat16* b1 = (const __nv_bfloat16*)d_in[6];
    const __nv_bfloat16* w2 = (const __nv_bfloat16*)d_in[7];
    const __nv_bfloat16* b2 = (const __nv_bfloat16*)d_in[8];
    const __nv_bfloat16* gate_w = (const __nv_bfloat16*)d_in[9];

    EncodeFn enc = nullptr;
    cudaDriverEntryPointQueryResult qr;
    cudaGetDriverEntryPoint("cuTensorMapEncodeTiled", (void**)&enc, cudaEnableDefault, &qr);
    void *p_h, *p_u, *p_o;
    cudaGetSymbolAddress(&p_h, g_h);
    cudaGetSymbolAddress(&p_u, g_u);
    cudaGetSymbolAddress(&p_o, g_o);

    CUtensorMap m_x, m_wqkv, m_h, m_w1, m_w2, m_u, m_o, m_wo, m_os, m_out;
    {
        uint64_t d[3] = {1024, 2048, 1}, s[2] = {2048, 2048 * 2048};
        uint32_t b[3] = {BK, 128, 1};
        make_map(enc, &m_x, x, 3, d, s, b, BK == 64 ? CU_TENSOR_MAP_SWIZZLE_128B : CU_TENSOR_MAP_SWIZZLE_64B);
    }
    {
        uint64_t d[2] = {1024, 2048}, s[1] = {2048};
        uint32_t b[2] = {64, 64};
        make_map(enc, &m_out, d_out, 2, d, s, b, CU_TENSOR_MAP_SWIZZLE_128B);
    }
    {
        uint64_t d[3] = {1024, 1024, 3}, s[2] = {6144, 2048};
        uint32_t b[3] = {64, BK, 3};
        make_map(enc, &m_wqkv, wqkv, 3, d, s, b, CU_TENSOR_MAP_SWIZZLE_128B);
    }
    {
        uint64_t d[3] = {64, 2048, 16}, s[2] = {2048, 128};
        uint32_t b[3] = {64, BK, 2};
        make_map(enc, &m_h, p_h, 3, d, s, b, CU_TENSOR_MAP_SWIZZLE_128B);
    }
    {
        uint64_t d[3] = {32, 2048, 112}, s[2] = {7168, 64};
        uint32_t b[3] = {32, BK, 7};
        make_map(enc, &m_w1, w1, 3, d, s, b, CU_TENSOR_MAP_SWIZZLE_64B);
    }
    {
        uint64_t d[3] = {64, 3584, 32}, s[2] = {4096, 128};
        uint32_t b[3] = {64, BK, 2};
        make_map(enc, &m_w2, w2, 3, d, s, b, CU_TENSOR_MAP_SWIZZLE_128B);
    }
    {
        uint64_t d[3] = {64, 3584, 16}, s[2] = {2048, 128};
        uint32_t b[3] = {64, BK, 4};
        make_map(enc, &m_u, p_u, 3, d, s, b, CU_TENSOR_MAP_SWIZZLE_128B);
    }
    {
        uint64_t d[3] = {64, 1024, 32}, s[2] = {4096, 128};
        uint32_t b[3] = {64, BK, 2};
        make_map(enc, &m_o, p_o, 3, d, s, b, CU_TENSOR_MAP_SWIZZLE_128B);
        uint32_t bs[3] = {64, 64, 2};
        make_map(enc, &m_os, p_o, 3, d, s, bs, CU_TENSOR_MAP_SWIZZLE_128B);
    }
    {
        uint64_t d[3] = {64, 1024, 16}, s[2] = {2048, 128};
        uint32_t b[3] = {64, BK, 4};
        make_map(enc, &m_wo, wo, 3, d, s, b, CU_TENSOR_MAP_SWIZZLE_128B);
    }
    Params prm{x, wphi, b1, b2, gate_w};

    cudaFuncSetAttribute(fused_kernel, cudaFuncAttributeMaxDynamicSharedMemorySize, SMEM_BYTES);
    fused_kernel<<<NCTA, NTHREADS, SMEM_BYTES, cudaStreamPerThread>>>(m_x, m_wqkv, m_h, m_w1, m_w2, m_u, m_o, m_wo, m_os, m_out, prm);
}
```
